```python
import torch

def _softmax(x, axis=-1):
    return torch.softmax(x, dim=axis)
def _gelu(x):
    return torch.nn.functional.gelu(x, approximate="tanh")
def _silu(x):
    return torch.nn.functional.silu(x)
def _sigmoid(x):
    return torch.sigmoid(x)
def _layernorm(x, axis=-1, eps=1e-5):
    m = x.mean(dim=axis, keepdim=True)
    v = x.var(dim=axis, keepdim=True, unbiased=False)
    return (x - m) / torch.sqrt(v + eps)
def _scatter_add(tgt, idx, src, axis=0):
    return tgt.clone().index_add_(axis, idx, src)
def _segment_sum(src, seg, n):
    out = torch.zeros((n,) + src.shape[1:], dtype=src.dtype)
    return out.index_add_(0, seg, src)
def _pad(x, pw):
    flat = tuple(v for pair in reversed(pw) for v in pair)
    return torch.nn.functional.pad(x, flat)

kernel_name = 'sequential_preLN__ssm_conv_h3__glu_gated_swiglu__prompt'

def setup_inputs():

    _w = (lambda a: (lambda t: t.to(torch.bfloat16) if t.is_floating_point() else t)(torch.as_tensor(a)))
    def _A_setup():
        B, S, D = 1, 2048, 640
        ks = 4
        return {
            "q": _w((lambda *s: torch.randn(*s, dtype=torch.bfloat16) * 0.05)(B, S, D)),
            "k": _w((lambda *s: torch.randn(*s, dtype=torch.bfloat16) * 0.2)(B, S, D)),
            "v": _w((lambda *s: torch.randn(*s, dtype=torch.bfloat16) * 0.2)(B, S, D)),
            "shift_k": _w((lambda *s: torch.randn(*s, dtype=torch.bfloat16) * 0.2)(D, ks) * 0.5),
            "ssm_k": _w((lambda *s: torch.randn(*s, dtype=torch.bfloat16) * 0.4)(D, S) * (1.0 / S ** 0.5)),
            "ssm_D": _w((lambda *s: torch.randn(*s, dtype=torch.bfloat16) * 0.2)(D)),
        }
    _A_in = _A_setup()

    def _B_setup():
        B, S, D, F = 1, 2048, 640, 1536
        return {
            "x": _w((lambda *s: torch.randn(*s, dtype=torch.bfloat16) * 0.05)(B, S, D)),
            "w1": _w((lambda *s: torch.randn(*s, dtype=torch.bfloat16) * 0.2)(D, F) * (2.0 / D) ** 0.5),
            "w3": _w((lambda *s: torch.randn(*s, dtype=torch.bfloat16) * 0.2)(D, F) * (2.0 / D) ** 0.5),
            "w2": _w((lambda *s: torch.randn(*s, dtype=torch.bfloat16) * 0.2)(F, D) * (2.0 / F) ** 0.5),
        }
    _B_in = _B_setup()

    return {
        "A_q": _A_in["q"],
        "A_k": _A_in["k"],
        "A_v": _A_in["v"],
        "A_shift_k": _A_in["shift_k"],
        "A_ssm_k": _A_in["ssm_k"],
        "A_ssm_D": _A_in["ssm_D"],
        "B_x": _B_in["x"],
        "B_w1": _B_in["w1"],
        "B_w3": _B_in["w3"],
        "B_w2": _B_in["w2"],
    }

def reference(A_q, A_k, A_v, A_shift_k, A_ssm_k, A_ssm_D, B_x, B_w1, B_w3, B_w2):
    def _A_ref(q, k, v, shift_k, ssm_k, ssm_D):
        B, S, D = q.shape
        ks = shift_k.shape[-1]
        k_pad = _pad(k, ((0, 0), (ks - 1, 0), (0, 0)))
        k_shift = torch.zeros_like(k)
        for t in range(ks):
            k_shift = k_shift + k_pad[:, t:t + S, :] * shift_k[:, ks - 1 - t][None, None, :]
        kv = k_shift * v
        L = 2 * S
        kv_pad = _pad(kv, ((0, 0), (0, S), (0, 0)))
        kf_pad = _pad(ssm_k, ((0, 0), (0, S)))
        kv_f = (lambda x, axes=(-2,-1): torch.fft.rfft2(x.float(), dim=axes))(kv_pad[:, None, :, :], axes=(1, 2))
        kf_f = (lambda x, axes=(-2,-1): torch.fft.rfft2(x.float(), dim=axes))(kf_pad[:, None, :], axes=(1, 2))
        kf_f = (lambda x, *d: x.permute(*d))(kf_f, 1, 2, 0)
        y_f = kv_f * kf_f[None, :, :, :]
        y = (lambda x, s, axes=(-2,-1): torch.fft.irfft2(x, s=s, dim=axes).to(torch.bfloat16))(y_f, (1, L), axes=(1, 2))[:, 0, :S, :]
        y = y + kv * ssm_D[None, None, :]
        return q * y

    def _B_ref(x, w1, w3, w2):
        gate = torch.einsum("bsd,df->bsf", x, w1)
        up = torch.einsum("bsd,df->bsf", x, w3)
        h = _silu(gate) * up
        out = torch.einsum("bsf,fd->bsd", h, w2)
        return out

    x = A_q
    h = x + _A_ref(_layernorm(x, axis=-1), A_k, A_v, A_shift_k, A_ssm_k, A_ssm_D)
    h2 = h + _B_ref(_layernorm(h, axis=-1), B_w1, B_w3, B_w2)
    return h2
```

```cpp
#include <cuda_runtime.h>
#include <cuda_bf16.h>
#include <cuda.h>
#include <stdint.h>

namespace {

constexpr int NCTA = 132;
constexpr float LN_EPS = 1e-5f;
#define AUX_DELAY 9500
#define W2PF_DELAY 9000
#define PF2 1
#define KVPF 0
#define KVPF_T0 500
#define KFPOS 1
#define MAP2 0
#define TILE_M(l) ((l) >> 3)
#define TILE_F(l) ((l) & 7)
#define P2K0 1
#define USE_TANH 1
#define NSCALE 0.5f
#define RSCALE 2.0f
#define HEADV 1
#define G2STAMP 0
#define P2D0 20
#define P2D1 20
#define KFPOSH 0
#define CR 168
#define P1K0 2
#define RELFIRST 1
#define MSTART 0
#define LATEN 34
#define NPOLL 0
#define W2N 42
#define W2KB 5
#define W2GN 6
#define W2AFT 1
#define WAVE_T0 3000
#define WAVE_DT 1000

__device__ __align__(1024) __nv_bfloat16 g_hT[640 * 2048];
__device__ __align__(1024) unsigned char g_g[16 * 24 * 16384];
__device__ __align__(1024) unsigned char g_w2t[8 * 245760];
__device__ __align__(128) float2 g_stat1[2048];
__device__ __align__(128) float2 g_stat2[2048 * 4];
__device__ __align__(128) float g_colsum[8 * 3 * 128];
__device__ __align__(128) unsigned g_hcnt[10 * 32];
__device__ __align__(128) unsigned g_gflag[16 * 32];
__device__ __align__(128) unsigned g_w2cnt[8 * 32];
__device__ __align__(128) unsigned g_done;
#define STAMP(i) do {} while (0)
#define STAMP0(i) do {} while (0)
#define GSTAMP(i) do {} while (0)

constexpr uint32_t OFF_A = 0;
constexpr uint32_t OFF_W = 163840;
constexpr uint32_t OFF_MISC = 229376;
constexpr uint32_t OFF_ST2 = OFF_MISC;
constexpr uint32_t OFF_CS = OFF_MISC + 1024;
constexpr uint32_t OFF_BAR = OFF_MISC + 2560;
constexpr uint32_t SMEM_BYTES = 232448;
constexpr uint32_t B_WFULL = OFF_BAR, B_WEMPTY = OFF_BAR + 32, B_AFULL = OFF_BAR + 64, B_AEMPTY = OFF_BAR + 144;
constexpr uint32_t B_S2 = OFF_BAR + 224, B_CS = OFF_BAR + 232  ;
constexpr uint32_t B_ERDY = OFF_BAR + 256  , B_W2G = OFF_BAR + 384, B_EDONE = OFF_BAR + 392, B_YRDY = OFF_BAR + 400  , B_KFL0 = OFF_BAR + 432, B_KFL = OFF_BAR + 440, B_KF = OFF_BAR + 448, B_CDONE = OFF_BAR + 456;
constexpr uint32_t B_KF0 = OFF_BAR + 464  , B_EP = OFF_BAR + 480, OFF_EP = OFF_BAR + 488, B_XFREE = OFF_BAR + 496, B_XIN = OFF_BAR + 504;
constexpr uint32_t B_TFULL = B_AFULL;
constexpr uint32_t TILE = 25600;
constexpr uint32_t REC = 1920, ECH = 320;
constexpr uint32_t OFF_OUT = TILE;
constexpr uint32_t PR = 4224, OFF_P = OFF_OUT + 8 * REC;
constexpr uint32_t KS = 4224, OFF_KFL = OFF_P + 12 * PR + 128;
constexpr uint32_t OFF_U = OFF_KFL - 128 + 2 * KS + REC;
constexpr uint32_t OFF_ID = OFF_U + 32 * REC, OFF_SH = OFF_ID + 128, OFF_D = OFF_SH + 128;
constexpr uint32_t OFF_KFE = OFF_W + 2 * TILE + 384;
static_assert(OFF_D + 32 <= OFF_W && (OFF_U & 63) == 0 && OFF_KFE + 3 * KS - 128 <= OFF_MISC && OFF_P + 4 * PR >= 49152, "layout");
__host__ __device__ constexpr uint32_t slot_off(uint32_t sl) { return sl ? OFF_W - TILE + sl * TILE : 0; }

__device__ __forceinline__ void mbar_init(uint32_t b, uint32_t c) { asm volatile("mbarrier.init.shared::cta.b64 [%0], %1;" ::"r"(b), "r"(c) : "memory"); }
__device__ __forceinline__ void mbar_expect(uint32_t b, uint32_t n) { asm volatile("mbarrier.arrive.expect_tx.shared::cta.b64 _, [%0], %1;" ::"r"(b), "r"(n) : "memory"); }
__device__ __forceinline__ void mbar_arrive(uint32_t b) { asm volatile("mbarrier.arrive.shared::cta.b64 _, [%0];" ::"r"(b) : "memory"); }
__device__ __forceinline__ void mbar_wait(uint32_t b, uint32_t par) {
  asm volatile(
      "{.reg .pred p; .reg .u32 c; mov.u32 c, 0;\n"
      "LW%=: mbarrier.try_wait.parity.shared::cta.b64 p, [%0], %1;\n"
      "@p bra LD%=;\n"
      "add.u32 c, c, 1; setp.lt.u32 p, c, 4000000; @p bra LW%=;\n"
      "trap;\n"
      "LD%=: }\n" ::"r"(b), "r"(par) : "memory");
}
__device__ __forceinline__ void mbar_wait_u(uint32_t b, uint32_t par) {
  asm volatile("{.reg .pred p;\nLW%=: mbarrier.try_wait.parity.shared::cta.b64 p, [%0], %1;\n@!p bra LW%=;}\n" ::"r"(b), "r"(par) : "memory");
}
__device__ __forceinline__ bool elect1() { uint32_t p; asm volatile("{.reg .pred P; elect.sync _|P, 0xffffffff; selp.u32 %0,1,0,P;}" : "=r"(p)); return p; }
__device__ __forceinline__ void bar_sync(int id, int n) { asm volatile("bar.sync %0, %1;" ::"r"(id), "r"(n) : "memory"); }
__device__ __forceinline__ void bar_arrive(int id, int n) { asm volatile("bar.arrive %0, %1;" ::"r"(id), "r"(n) : "memory"); }
__device__ __forceinline__ void fence_async_s() { asm volatile("fence.proxy.async.shared::cta;" ::: "memory"); }
__device__ __forceinline__ void fence_async_g() { asm volatile("fence.acquire.gpu;\nfence.proxy.async.global;" ::: "memory"); }
__device__ __forceinline__ void fence_rel() { asm volatile("fence.release.gpu;" ::: "memory"); }
__device__ __forceinline__ int tid_x() { int v; asm volatile("mov.u32 %0, %%tid.x;" : "=r"(v)); return v; }
__device__ __forceinline__ void cl_arrive_rlx() { asm volatile("barrier.cluster.arrive.relaxed.aligned;" ::: "memory"); }
__device__ __forceinline__ void cl_wait() { asm volatile("barrier.cluster.wait.acquire.aligned;" ::: "memory"); }
__device__ __forceinline__ uint32_t mapa(uint32_t a, uint32_t r) { uint32_t o; asm volatile("mapa.shared::cluster.u32 %0, %1, %2;" : "=r"(o) : "r"(a), "r"(r)); return o; }
__device__ __forceinline__ void mbar_arrive_n(uint32_t b, uint32_t n) { asm volatile("mbarrier.arrive.shared::cta.b64 _, [%0], %1;" ::"r"(b), "r"(n) : "memory"); }
__device__ __forceinline__ bool mbar_test(uint32_t b, uint32_t par) {
  uint32_t ok; asm volatile("{.reg .pred p; mbarrier.test_wait.parity.shared::cta.b64 p, [%1], %2; selp.u32 %0,1,0,p;}" : "=r"(ok) : "r"(b), "r"(par) : "memory"); return __all_sync(0xffffffff, ok);
}
__device__ __forceinline__ void st_async4(uint32_t a, uint32_t x, uint32_t y, uint32_t z, uint32_t w, uint32_t bar) {
  asm volatile("st.async.weak.shared::cluster.mbarrier::complete_tx::bytes.v4.b32 [%0], {%1,%2,%3,%4}, [%5];" ::"r"(a), "r"(x), "r"(y), "r"(z), "r"(w), "r"(bar) : "memory");
}
__device__ __forceinline__ void stsm2t(uint32_t a, uint32_t r0, uint32_t r1) {
  asm volatile("stmatrix.sync.aligned.m8n8.x2.trans.shared.b16 [%0], {%1,%2};" ::"r"(a), "r"(r0), "r"(r1) : "memory");
}
__device__ __forceinline__ uint4 ldg128(const void* p) { uint4 v; asm volatile("ld.global.nc.v4.u32 {%0,%1,%2,%3}, [%4];" : "=r"(v.x), "=r"(v.y), "=r"(v.z), "=r"(v.w) : "l"(p)); return v; }
__device__ __forceinline__ void stg128(void* p, uint4 v) { asm volatile("st.global.v4.b32 [%0], {%1,%2,%3,%4};" ::"l"(p), "r"(v.x), "r"(v.y), "r"(v.z), "r"(v.w) : "memory"); }
__device__ __forceinline__ void prefetch_tm(const CUtensorMap* t) { asm volatile("prefetch.tensormap [%0];" ::"l"(t) : "memory"); }
__device__ __forceinline__ uint32_t lds32(uint32_t a) { uint32_t v; asm volatile("ld.shared.b32 %0, [%1];" : "=r"(v) : "r"(a) : "memory"); return v; }
__device__ __forceinline__ uint2 lds64(uint32_t a) { uint2 v; asm volatile("ld.shared.v2.b32 {%0,%1}, [%2];" : "=r"(v.x), "=r"(v.y) : "r"(a) : "memory"); return v; }
__device__ __forceinline__ uint4 lds128(uint32_t a) { uint4 v; asm volatile("ld.shared.v4.b32 {%0,%1,%2,%3}, [%4];" : "=r"(v.x), "=r"(v.y), "=r"(v.z), "=r"(v.w) : "r"(a) : "memory"); return v; }
__device__ __forceinline__ float4 lds128f(uint32_t a) { float4 v; asm volatile("ld.shared.v4.f32 {%0,%1,%2,%3}, [%4];" : "=f"(v.x), "=f"(v.y), "=f"(v.z), "=f"(v.w) : "r"(a) : "memory"); return v; }
__device__ __forceinline__ float2 lds64f(uint32_t a) { float2 v; asm volatile("ld.shared.v2.f32 {%0,%1}, [%2];" : "=f"(v.x), "=f"(v.y) : "r"(a) : "memory"); return v; }
__device__ __forceinline__ void sts32f(uint32_t a, float v) { asm volatile("st.shared.f32 [%0], %1;" ::"r"(a), "f"(v) : "memory"); }
__device__ __forceinline__ void sts32(uint32_t a, uint32_t v) { asm volatile("st.shared.b32 [%0], %1;" ::"r"(a), "r"(v) : "memory"); }
__device__ __forceinline__ void sts64f(uint32_t a, float x, float y) { asm volatile("st.shared.v2.f32 [%0], {%1,%2};" ::"r"(a), "f"(x), "f"(y) : "memory"); }
__device__ __forceinline__ void sts128(uint32_t a, uint4 v) { asm volatile("st.shared.v4.b32 [%0], {%1,%2,%3,%4};" ::"r"(a), "r"(v.x), "r"(v.y), "r"(v.z), "r"(v.w) : "memory"); }
__device__ __forceinline__ void ldsm4t(uint32_t a, uint32_t& r0, uint32_t& r1, uint32_t& r2, uint32_t& r3) {
  asm volatile("ldmatrix.sync.aligned.m8n8.x4.trans.shared.b16 {%0,%1,%2,%3}, [%4];" : "=r"(r0), "=r"(r1), "=r"(r2), "=r"(r3) : "r"(a) : "memory");
}
__device__ __forceinline__ void stsm4(uint32_t a, uint32_t r0, uint32_t r1, uint32_t r2, uint32_t r3) {
  asm volatile("stmatrix.sync.aligned.m8n8.x4.shared.b16 [%0], {%1,%2,%3,%4};" ::"r"(a), "r"(r0), "r"(r1), "r"(r2), "r"(r3) : "memory");
}
__device__ __forceinline__ void bulk_g2s(uint32_t d, const void* g, uint32_t n, uint32_t bar) {
  asm volatile("cp.async.bulk.shared::cluster.global.mbarrier::complete_tx::bytes [%0], [%1], %2, [%3];" ::"r"(d), "l"(g), "r"(n), "r"(bar) : "memory");
}
__device__ __forceinline__ void tma2d(uint32_t d, const CUtensorMap* t, int c0, int c1, uint32_t bar) {
  asm volatile("cp.async.bulk.tensor.2d.shared::cluster.global.mbarrier::complete_tx::bytes [%0], [%1, {%3, %4}], [%2];" ::"r"(d), "l"(t), "r"(bar), "r"(c0), "r"(c1) : "memory");
}
__device__ __forceinline__ void tma3d(uint32_t d, const CUtensorMap* t, int c0, int kb, uint32_t bar) {
  asm volatile("cp.async.bulk.tensor.3d.shared::cluster.global.mbarrier::complete_tx::bytes [%0], [%1, {%3, %4, %5}], [%2];" ::"r"(d), "l"(t), "r"(bar), "r"(c0), "r"((kb & 1) * 64), "r"(kb >> 1) : "memory");
}
#define WAITLOOP(b, par) "mov.u32 c, 0;\nLW%=: mbarrier.try_wait.parity.shared::cta.b64 p, [" b "], " par ";\n@p bra LD%=;\nadd.u32 c, c, 1; setp.lt.u32 p, c, 4000000; @p bra LW%=;\ntrap;\nLD%=:\n"
__device__ __forceinline__ void wait_w13(uint32_t be, uint32_t par, uint32_t d, uint32_t d2, const CUtensorMap* t1, const CUtensorMap* t3, int c0, int c1, int c2, uint32_t bf) {
  asm volatile("{.reg .pred p; .reg .u32 c;\n" WAITLOOP("%0", "%1")
               "cp.async.bulk.tensor.3d.shared::cluster.global.mbarrier::complete_tx::bytes [%2], [%4, {%6, %7, %8}], [%9];\n"
               "cp.async.bulk.tensor.3d.shared::cluster.global.mbarrier::complete_tx::bytes [%3], [%5, {%6, %7, %8}], [%9];\n"
               "mbarrier.arrive.expect_tx.shared::cta.b64 _, [%9], 16384;}\n"
               ::"r"(be), "r"(par), "r"(d), "r"(d2), "l"(t1), "l"(t3), "r"(c0), "r"(c1), "r"(c2), "r"(bf) : "memory");
}
__device__ __forceinline__ void wait_bulk(uint32_t be, uint32_t par, uint32_t d, const void* g, uint32_t n, uint32_t bf) {
  asm volatile("{.reg .pred p; .reg .u32 c;\n" WAITLOOP("%0", "%1")
               "cp.async.bulk.shared::cluster.global.mbarrier::complete_tx::bytes [%2], [%3], %4, [%5];\n"
               "mbarrier.arrive.expect_tx.shared::cta.b64 _, [%5], %4;}\n"
               ::"r"(be), "r"(par), "r"(d), "l"(g), "r"(n), "r"(bf) : "memory");
}
__device__ __forceinline__ void tma4d(uint32_t d, const CUtensorMap* t, int c0, int c2, int c3, uint32_t bar) {
  asm volatile("cp.async.bulk.tensor.4d.shared::cluster.global.mbarrier::complete_tx::bytes [%0], [%1, {%3, %6, %4, %5}], [%2];" ::"r"(d), "l"(t), "r"(bar), "r"(c0), "r"(c2), "r"(c3), "r"(0) : "memory");
}
__device__ __forceinline__ void prefetch_l2(const void* g, uint32_t n) { asm volatile("cp.async.bulk.prefetch.L2.global [%0], %1;" ::"l"(g), "r"(n) : "memory"); }
__device__ __forceinline__ unsigned ld_relaxed(const unsigned* p) { unsigned v; asm volatile("ld.relaxed.gpu.global.u32 %0, [%1];" : "=r"(v) : "l"(p) : "memory"); return v; }
__device__ __forceinline__ uint2 ld_relaxed64(const void* p) { unsigned long long v; asm volatile("ld.relaxed.gpu.global.u64 %0, [%1];" : "=l"(v) : "l"(p) : "memory"); return make_uint2((uint32_t)v, (uint32_t)(v >> 32)); }
__device__ __forceinline__ void st_relaxed64(void* p, uint32_t lo, uint32_t hi) { unsigned long long v = lo | ((unsigned long long)hi << 32); asm volatile("st.relaxed.gpu.global.u64 [%0], %1;" ::"l"(p), "l"(v) : "memory"); }
__device__ __forceinline__ void st_relaxed(unsigned* p, unsigned v) { asm volatile("st.relaxed.gpu.global.u32 [%0], %1;" ::"l"(p), "r"(v) : "memory"); }
__device__ __forceinline__ void red_add(unsigned* p, unsigned v) { asm volatile("red.relaxed.gpu.global.add.u32 [%0], %1;" ::"l"(p), "r"(v) : "memory"); }
__device__ __forceinline__ uint32_t prmt(uint32_t a, uint32_t b, uint32_t s) { uint32_t o; asm("prmt.b32 %0, %1, %2, %3;" : "=r"(o) : "r"(a), "r"(b), "r"(s)); return o; }
__device__ __forceinline__ uint32_t hmul2(uint32_t a, uint32_t b) { uint32_t o; asm("mul.rn.bf16x2 %0, %1, %2;" : "=r"(o) : "r"(a), "r"(b)); return o; }
__device__ __forceinline__ uint32_t hfma2(uint32_t a, uint32_t b, uint32_t c) { uint32_t o; asm("fma.rn.bf16x2 %0, %1, %2, %3;" : "=r"(o) : "r"(a), "r"(b), "r"(c)); return o; }
__device__ __forceinline__ uint32_t shiftmul(__nv_bfloat162 wa, __nv_bfloat162 wb, uint32_t k0, uint32_t k1, uint32_t k2, uint32_t k3, uint32_t v) {
  typedef const __nv_bfloat162& R;
  __nv_bfloat162 a = __hmul2(__high2bfloat162(wb), reinterpret_cast<R>(k3));
  a = __hfma2(__low2bfloat162(wb), reinterpret_cast<R>(k2), a);
  a = __hfma2(__high2bfloat162(wa), reinterpret_cast<R>(k1), a);
  a = __hfma2(__low2bfloat162(wa), reinterpret_cast<R>(k0), a);
  a = __hmul2(a, reinterpret_cast<R>(v));
  return reinterpret_cast<const uint32_t&>(a);
}
__device__ __forceinline__ uint32_t packbf(float lo, float hi) { uint32_t o; asm("cvt.rn.bf16x2.f32 %0, %1, %2;" : "=r"(o) : "f"(hi), "f"(lo)); return o; }
__device__ __forceinline__ float bflo(uint32_t v) { return __uint_as_float(v << 16); }
__device__ __forceinline__ float bfhi(uint32_t v) { return __uint_as_float(v & 0xffff0000u); }
__device__ __forceinline__ uint64_t mkdesc(uint32_t addr, uint32_t lbo, uint32_t sbo, uint32_t sw) {
  return (uint64_t)((addr & 0x3FFFF) >> 4) | ((uint64_t)(lbo >> 4) << 16) | ((uint64_t)(sbo >> 4) << 32) | ((uint64_t)sw << 62);
}
__device__ __forceinline__ void wg_fence() { asm volatile("wgmma.fence.sync.aligned;" ::: "memory"); }
__device__ __forceinline__ void wg_commit() { asm volatile("wgmma.commit_group.sync.aligned;" ::: "memory"); }
template <int N> __device__ __forceinline__ void wg_wait() { asm volatile("wgmma.wait_group.sync.aligned %0;" ::"n"(N) : "memory"); }
__device__ __forceinline__ uint32_t xz(uint32_t v, uint32_t z) { uint32_t o; asm volatile("xor.b32 %0, %1, %2;" : "=r"(o) : "r"(v), "r"(z)); return o; }
__device__ __forceinline__ uint32_t xz3(uint32_t v, uint32_t d, uint32_t z) { uint32_t o; asm volatile("lop3.b32 %0, %1, %2, %3, 0x78;" : "=r"(o) : "r"(v), "r"(d), "r"(z)); return o; }
#define SPIN_GUARD(c) do { ++(c); asm volatile("{.reg .pred p; setp.gt.u32 p, %0, 4000000; @p trap;}" ::"r"(c)); } while (0)

template<int N> struct WRS;
template<> struct WRS<8>{ static __device__ __forceinline__ void f(float* d, uint32_t a0, uint32_t a1, uint32_t a2, uint32_t a3, uint64_t db, int sd){
  asm volatile("{.reg .pred p; setp.ne.b32 p, %9, 0;\n"
  "wgmma.mma_async.sync.aligned.m64n8k16.f32.bf16.bf16 {%0,%1,%2,%3}, {%4,%5,%6,%7}, %8, p, 1, 1, 0;}\n"
  : "+f"(d[0]),"+f"(d[1]),"+f"(d[2]),"+f"(d[3]) : "r"(a0),"r"(a1),"r"(a2),"r"(a3),"l"(db),"r"(sd)); } };
template<> struct WRS<16>{ static __device__ __forceinline__ void f(float* d, uint32_t a0, uint32_t a1, uint32_t a2, uint32_t a3, uint64_t db, int sd){
  asm volatile("{.reg .pred p; setp.ne.b32 p, %13, 0;\n"
  "wgmma.mma_async.sync.aligned.m64n16k16.f32.bf16.bf16 {%0,%1,%2,%3,%4,%5,%6,%7}, {%8,%9,%10,%11}, %12, p, 1, 1, 0;}\n"
  : "+f"(d[0]),"+f"(d[1]),"+f"(d[2]),"+f"(d[3]),"+f"(d[4]),"+f"(d[5]),"+f"(d[6]),"+f"(d[7]) : "r"(a0),"r"(a1),"r"(a2),"r"(a3),"l"(db),"r"(sd)); } };
template<> struct WRS<24>{ static __device__ __forceinline__ void f(float* d, uint32_t a0, uint32_t a1, uint32_t a2, uint32_t a3, uint64_t db, int sd){
  asm volatile("{.reg .pred p; setp.ne.b32 p, %17, 0;\n"
  "wgmma.mma_async.sync.aligned.m64n24k16.f32.bf16.bf16 {%0,%1,%2,%3,%4,%5,%6,%7,%8,%9,%10,%11}, {%12,%13,%14,%15}, %16, p, 1, 1, 0;}\n"
  : "+f"(d[0]),"+f"(d[1]),"+f"(d[2]),"+f"(d[3]),"+f"(d[4]),"+f"(d[5]),"+f"(d[6]),"+f"(d[7]),"+f"(d[8]),"+f"(d[9]),"+f"(d[10]),"+f"(d[11]) : "r"(a0),"r"(a1),"r"(a2),"r"(a3),"l"(db),"r"(sd)); } };
template<> struct WRS<32>{ static __device__ __forceinline__ void f(float* d, uint32_t a0, uint32_t a1, uint32_t a2, uint32_t a3, uint64_t db, int sd){
  asm volatile("{.reg .pred p; setp.ne.b32 p, %21, 0;\n"
  "wgmma.mma_async.sync.aligned.m64n32k16.f32.bf16.bf16 {%0,%1,%2,%3,%4,%5,%6,%7,%8,%9,%10,%11,%12,%13,%14,%15}, {%16,%17,%18,%19}, %20, p, 1, 1, 0;}\n"
  : "+f"(d[0]),"+f"(d[1]),"+f"(d[2]),"+f"(d[3]),"+f"(d[4]),"+f"(d[5]),"+f"(d[6]),"+f"(d[7]),"+f"(d[8]),"+f"(d[9]),"+f"(d[10]),"+f"(d[11]),"+f"(d[12]),"+f"(d[13]),"+f"(d[14]),"+f"(d[15]) : "r"(a0),"r"(a1),"r"(a2),"r"(a3),"l"(db),"r"(sd)); } };
template<> struct WRS<40>{ static __device__ __forceinline__ void f(float* d, uint32_t a0, uint32_t a1, uint32_t a2, uint32_t a3, uint64_t db, int sd){
  asm volatile("{.reg .pred p; setp.ne.b32 p, %25, 0;\n"
  "wgmma.mma_async.sync.aligned.m64n40k16.f32.bf16.bf16 {%0,%1,%2,%3,%4,%5,%6,%7,%8,%9,%10,%11,%12,%13,%14,%15,%16,%17,%18,%19}, {%20,%21,%22,%23}, %24, p, 1, 1, 0;}\n"
  : "+f"(d[0]),"+f"(d[1]),"+f"(d[2]),"+f"(d[3]),"+f"(d[4]),"+f"(d[5]),"+f"(d[6]),"+f"(d[7]),"+f"(d[8]),"+f"(d[9]),"+f"(d[10]),"+f"(d[11]),"+f"(d[12]),"+f"(d[13]),"+f"(d[14]),"+f"(d[15]),"+f"(d[16]),"+f"(d[17]),"+f"(d[18]),"+f"(d[19]) : "r"(a0),"r"(a1),"r"(a2),"r"(a3),"l"(db),"r"(sd)); } };
template<> struct WRS<48>{ static __device__ __forceinline__ void f(float* d, uint32_t a0, uint32_t a1, uint32_t a2, uint32_t a3, uint64_t db, int sd){
  asm volatile("{.reg .pred p; setp.ne.b32 p, %29, 0;\n"
  "wgmma.mma_async.sync.aligned.m64n48k16.f32.bf16.bf16 {%0,%1,%2,%3,%4,%5,%6,%7,%8,%9,%10,%11,%12,%13,%14,%15,%16,%17,%18,%19,%20,%21,%22,%23}, {%24,%25,%26,%27}, %28, p, 1, 1, 0;}\n"
  : "+f"(d[0]),"+f"(d[1]),"+f"(d[2]),"+f"(d[3]),"+f"(d[4]),"+f"(d[5]),"+f"(d[6]),"+f"(d[7]),"+f"(d[8]),"+f"(d[9]),"+f"(d[10]),"+f"(d[11]),"+f"(d[12]),"+f"(d[13]),"+f"(d[14]),"+f"(d[15]),"+f"(d[16]),"+f"(d[17]),"+f"(d[18]),"+f"(d[19]),"+f"(d[20]),"+f"(d[21]),"+f"(d[22]),"+f"(d[23]) : "r"(a0),"r"(a1),"r"(a2),"r"(a3),"l"(db),"r"(sd)); } };
template<> struct WRS<56>{ static __device__ __forceinline__ void f(float* d, uint32_t a0, uint32_t a1, uint32_t a2, uint32_t a3, uint64_t db, int sd){
  asm volatile("{.reg .pred p; setp.ne.b32 p, %33, 0;\n"
  "wgmma.mma_async.sync.aligned.m64n56k16.f32.bf16.bf16 {%0,%1,%2,%3,%4,%5,%6,%7,%8,%9,%10,%11,%12,%13,%14,%15,%16,%17,%18,%19,%20,%21,%22,%23,%24,%25,%26,%27}, {%28,%29,%30,%31}, %32, p, 1, 1, 0;}\n"
  : "+f"(d[0]),"+f"(d[1]),"+f"(d[2]),"+f"(d[3]),"+f"(d[4]),"+f"(d[5]),"+f"(d[6]),"+f"(d[7]),"+f"(d[8]),"+f"(d[9]),"+f"(d[10]),"+f"(d[11]),"+f"(d[12]),"+f"(d[13]),"+f"(d[14]),"+f"(d[15]),"+f"(d[16]),"+f"(d[17]),"+f"(d[18]),"+f"(d[19]),"+f"(d[20]),"+f"(d[21]),"+f"(d[22]),"+f"(d[23]),"+f"(d[24]),"+f"(d[25]),"+f"(d[26]),"+f"(d[27]) : "r"(a0),"r"(a1),"r"(a2),"r"(a3),"l"(db),"r"(sd)); } };
template<> struct WRS<64>{ static __device__ __forceinline__ void f(float* d, uint32_t a0, uint32_t a1, uint32_t a2, uint32_t a3, uint64_t db, int sd){
  asm volatile("{.reg .pred p; setp.ne.b32 p, %37, 0;\n"
  "wgmma.mma_async.sync.aligned.m64n64k16.f32.bf16.bf16 {%0,%1,%2,%3,%4,%5,%6,%7,%8,%9,%10,%11,%12,%13,%14,%15,%16,%17,%18,%19,%20,%21,%22,%23,%24,%25,%26,%27,%28,%29,%30,%31}, {%32,%33,%34,%35}, %36, p, 1, 1, 0;}\n"
  : "+f"(d[0]),"+f"(d[1]),"+f"(d[2]),"+f"(d[3]),"+f"(d[4]),"+f"(d[5]),"+f"(d[6]),"+f"(d[7]),"+f"(d[8]),"+f"(d[9]),"+f"(d[10]),"+f"(d[11]),"+f"(d[12]),"+f"(d[13]),"+f"(d[14]),"+f"(d[15]),"+f"(d[16]),"+f"(d[17]),"+f"(d[18]),"+f"(d[19]),"+f"(d[20]),"+f"(d[21]),"+f"(d[22]),"+f"(d[23]),"+f"(d[24]),"+f"(d[25]),"+f"(d[26]),"+f"(d[27]),"+f"(d[28]),"+f"(d[29]),"+f"(d[30]),"+f"(d[31]) : "r"(a0),"r"(a1),"r"(a2),"r"(a3),"l"(db),"r"(sd)); } };
template<> struct WRS<72>{ static __device__ __forceinline__ void f(float* d, uint32_t a0, uint32_t a1, uint32_t a2, uint32_t a3, uint64_t db, int sd){
  asm volatile("{.reg .pred p; setp.ne.b32 p, %41, 0;\n"
  "wgmma.mma_async.sync.aligned.m64n72k16.f32.bf16.bf16 {%0,%1,%2,%3,%4,%5,%6,%7,%8,%9,%10,%11,%12,%13,%14,%15,%16,%17,%18,%19,%20,%21,%22,%23,%24,%25,%26,%27,%28,%29,%30,%31,%32,%33,%34,%35}, {%36,%37,%38,%39}, %40, p, 1, 1, 0;}\n"
  : "+f"(d[0]),"+f"(d[1]),"+f"(d[2]),"+f"(d[3]),"+f"(d[4]),"+f"(d[5]),"+f"(d[6]),"+f"(d[7]),"+f"(d[8]),"+f"(d[9]),"+f"(d[10]),"+f"(d[11]),"+f"(d[12]),"+f"(d[13]),"+f"(d[14]),"+f"(d[15]),"+f"(d[16]),"+f"(d[17]),"+f"(d[18]),"+f"(d[19]),"+f"(d[20]),"+f"(d[21]),"+f"(d[22]),"+f"(d[23]),"+f"(d[24]),"+f"(d[25]),"+f"(d[26]),"+f"(d[27]),"+f"(d[28]),"+f"(d[29]),"+f"(d[30]),"+f"(d[31]),"+f"(d[32]),"+f"(d[33]),"+f"(d[34]),"+f"(d[35]) : "r"(a0),"r"(a1),"r"(a2),"r"(a3),"l"(db),"r"(sd)); } };
template<> struct WRS<80>{ static __device__ __forceinline__ void f(float* d, uint32_t a0, uint32_t a1, uint32_t a2, uint32_t a3, uint64_t db, int sd){
  asm volatile("{.reg .pred p; setp.ne.b32 p, %45, 0;\n"
  "wgmma.mma_async.sync.aligned.m64n80k16.f32.bf16.bf16 {%0,%1,%2,%3,%4,%5,%6,%7,%8,%9,%10,%11,%12,%13,%14,%15,%16,%17,%18,%19,%20,%21,%22,%23,%24,%25,%26,%27,%28,%29,%30,%31,%32,%33,%34,%35,%36,%37,%38,%39}, {%40,%41,%42,%43}, %44, p, 1, 1, 0;}\n"
  : "+f"(d[0]),"+f"(d[1]),"+f"(d[2]),"+f"(d[3]),"+f"(d[4]),"+f"(d[5]),"+f"(d[6]),"+f"(d[7]),"+f"(d[8]),"+f"(d[9]),"+f"(d[10]),"+f"(d[11]),"+f"(d[12]),"+f"(d[13]),"+f"(d[14]),"+f"(d[15]),"+f"(d[16]),"+f"(d[17]),"+f"(d[18]),"+f"(d[19]),"+f"(d[20]),"+f"(d[21]),"+f"(d[22]),"+f"(d[23]),"+f"(d[24]),"+f"(d[25]),"+f"(d[26]),"+f"(d[27]),"+f"(d[28]),"+f"(d[29]),"+f"(d[30]),"+f"(d[31]),"+f"(d[32]),"+f"(d[33]),"+f"(d[34]),"+f"(d[35]),"+f"(d[36]),"+f"(d[37]),"+f"(d[38]),"+f"(d[39]) : "r"(a0),"r"(a1),"r"(a2),"r"(a3),"l"(db),"r"(sd)); } };
template<> struct WRS<88>{ static __device__ __forceinline__ void f(float* d, uint32_t a0, uint32_t a1, uint32_t a2, uint32_t a3, uint64_t db, int sd){
  asm volatile("{.reg .pred p; setp.ne.b32 p, %49, 0;\n"
  "wgmma.mma_async.sync.aligned.m64n88k16.f32.bf16.bf16 {%0,%1,%2,%3,%4,%5,%6,%7,%8,%9,%10,%11,%12,%13,%14,%15,%16,%17,%18,%19,%20,%21,%22,%23,%24,%25,%26,%27,%28,%29,%30,%31,%32,%33,%34,%35,%36,%37,%38,%39,%40,%41,%42,%43}, {%44,%45,%46,%47}, %48, p, 1, 1, 0;}\n"
  : "+f"(d[0]),"+f"(d[1]),"+f"(d[2]),"+f"(d[3]),"+f"(d[4]),"+f"(d[5]),"+f"(d[6]),"+f"(d[7]),"+f"(d[8]),"+f"(d[9]),"+f"(d[10]),"+f"(d[11]),"+f"(d[12]),"+f"(d[13]),"+f"(d[14]),"+f"(d[15]),"+f"(d[16]),"+f"(d[17]),"+f"(d[18]),"+f"(d[19]),"+f"(d[20]),"+f"(d[21]),"+f"(d[22]),"+f"(d[23]),"+f"(d[24]),"+f"(d[25]),"+f"(d[26]),"+f"(d[27]),"+f"(d[28]),"+f"(d[29]),"+f"(d[30]),"+f"(d[31]),"+f"(d[32]),"+f"(d[33]),"+f"(d[34]),"+f"(d[35]),"+f"(d[36]),"+f"(d[37]),"+f"(d[38]),"+f"(d[39]),"+f"(d[40]),"+f"(d[41]),"+f"(d[42]),"+f"(d[43]) : "r"(a0),"r"(a1),"r"(a2),"r"(a3),"l"(db),"r"(sd)); } };
template<> struct WRS<96>{ static __device__ __forceinline__ void f(float* d, uint32_t a0, uint32_t a1, uint32_t a2, uint32_t a3, uint64_t db, int sd){
  asm volatile("{.reg .pred p; setp.ne.b32 p, %53, 0;\n"
  "wgmma.mma_async.sync.aligned.m64n96k16.f32.bf16.bf16 {%0,%1,%2,%3,%4,%5,%6,%7,%8,%9,%10,%11,%12,%13,%14,%15,%16,%17,%18,%19,%20,%21,%22,%23,%24,%25,%26,%27,%28,%29,%30,%31,%32,%33,%34,%35,%36,%37,%38,%39,%40,%41,%42,%43,%44,%45,%46,%47}, {%48,%49,%50,%51}, %52, p, 1, 1, 0;}\n"
  : "+f"(d[0]),"+f"(d[1]),"+f"(d[2]),"+f"(d[3]),"+f"(d[4]),"+f"(d[5]),"+f"(d[6]),"+f"(d[7]),"+f"(d[8]),"+f"(d[9]),"+f"(d[10]),"+f"(d[11]),"+f"(d[12]),"+f"(d[13]),"+f"(d[14]),"+f"(d[15]),"+f"(d[16]),"+f"(d[17]),"+f"(d[18]),"+f"(d[19]),"+f"(d[20]),"+f"(d[21]),"+f"(d[22]),"+f"(d[23]),"+f"(d[24]),"+f"(d[25]),"+f"(d[26]),"+f"(d[27]),"+f"(d[28]),"+f"(d[29]),"+f"(d[30]),"+f"(d[31]),"+f"(d[32]),"+f"(d[33]),"+f"(d[34]),"+f"(d[35]),"+f"(d[36]),"+f"(d[37]),"+f"(d[38]),"+f"(d[39]),"+f"(d[40]),"+f"(d[41]),"+f"(d[42]),"+f"(d[43]),"+f"(d[44]),"+f"(d[45]),"+f"(d[46]),"+f"(d[47]) : "r"(a0),"r"(a1),"r"(a2),"r"(a3),"l"(db),"r"(sd)); } };
template<> struct WRS<104>{ static __device__ __forceinline__ void f(float* d, uint32_t a0, uint32_t a1, uint32_t a2, uint32_t a3, uint64_t db, int sd){
  asm volatile("{.reg .pred p; setp.ne.b32 p, %57, 0;\n"
  "wgmma.mma_async.sync.aligned.m64n104k16.f32.bf16.bf16 {%0,%1,%2,%3,%4,%5,%6,%7,%8,%9,%10,%11,%12,%13,%14,%15,%16,%17,%18,%19,%20,%21,%22,%23,%24,%25,%26,%27,%28,%29,%30,%31,%32,%33,%34,%35,%36,%37,%38,%39,%40,%41,%42,%43,%44,%45,%46,%47,%48,%49,%50,%51}, {%52,%53,%54,%55}, %56, p, 1, 1, 0;}\n"
  : "+f"(d[0]),"+f"(d[1]),"+f"(d[2]),"+f"(d[3]),"+f"(d[4]),"+f"(d[5]),"+f"(d[6]),"+f"(d[7]),"+f"(d[8]),"+f"(d[9]),"+f"(d[10]),"+f"(d[11]),"+f"(d[12]),"+f"(d[13]),"+f"(d[14]),"+f"(d[15]),"+f"(d[16]),"+f"(d[17]),"+f"(d[18]),"+f"(d[19]),"+f"(d[20]),"+f"(d[21]),"+f"(d[22]),"+f"(d[23]),"+f"(d[24]),"+f"(d[25]),"+f"(d[26]),"+f"(d[27]),"+f"(d[28]),"+f"(d[29]),"+f"(d[30]),"+f"(d[31]),"+f"(d[32]),"+f"(d[33]),"+f"(d[34]),"+f"(d[35]),"+f"(d[36]),"+f"(d[37]),"+f"(d[38]),"+f"(d[39]),"+f"(d[40]),"+f"(d[41]),"+f"(d[42]),"+f"(d[43]),"+f"(d[44]),"+f"(d[45]),"+f"(d[46]),"+f"(d[47]),"+f"(d[48]),"+f"(d[49]),"+f"(d[50]),"+f"(d[51]) : "r"(a0),"r"(a1),"r"(a2),"r"(a3),"l"(db),"r"(sd)); } };
template<> struct WRS<112>{ static __device__ __forceinline__ void f(float* d, uint32_t a0, uint32_t a1, uint32_t a2, uint32_t a3, uint64_t db, int sd){
  asm volatile("{.reg .pred p; setp.ne.b32 p, %61, 0;\n"
  "wgmma.mma_async.sync.aligned.m64n112k16.f32.bf16.bf16 {%0,%1,%2,%3,%4,%5,%6,%7,%8,%9,%10,%11,%12,%13,%14,%15,%16,%17,%18,%19,%20,%21,%22,%23,%24,%25,%26,%27,%28,%29,%30,%31,%32,%33,%34,%35,%36,%37,%38,%39,%40,%41,%42,%43,%44,%45,%46,%47,%48,%49,%50,%51,%52,%53,%54,%55}, {%56,%57,%58,%59}, %60, p, 1, 1, 0;}\n"
  : "+f"(d[0]),"+f"(d[1]),"+f"(d[2]),"+f"(d[3]),"+f"(d[4]),"+f"(d[5]),"+f"(d[6]),"+f"(d[7]),"+f"(d[8]),"+f"(d[9]),"+f"(d[10]),"+f"(d[11]),"+f"(d[12]),"+f"(d[13]),"+f"(d[14]),"+f"(d[15]),"+f"(d[16]),"+f"(d[17]),"+f"(d[18]),"+f"(d[19]),"+f"(d[20]),"+f"(d[21]),"+f"(d[22]),"+f"(d[23]),"+f"(d[24]),"+f"(d[25]),"+f"(d[26]),"+f"(d[27]),"+f"(d[28]),"+f"(d[29]),"+f"(d[30]),"+f"(d[31]),"+f"(d[32]),"+f"(d[33]),"+f"(d[34]),"+f"(d[35]),"+f"(d[36]),"+f"(d[37]),"+f"(d[38]),"+f"(d[39]),"+f"(d[40]),"+f"(d[41]),"+f"(d[42]),"+f"(d[43]),"+f"(d[44]),"+f"(d[45]),"+f"(d[46]),"+f"(d[47]),"+f"(d[48]),"+f"(d[49]),"+f"(d[50]),"+f"(d[51]),"+f"(d[52]),"+f"(d[53]),"+f"(d[54]),"+f"(d[55]) : "r"(a0),"r"(a1),"r"(a2),"r"(a3),"l"(db),"r"(sd)); } };
template<> struct WRS<120>{ static __device__ __forceinline__ void f(float* d, uint32_t a0, uint32_t a1, uint32_t a2, uint32_t a3, uint64_t db, int sd){
  asm volatile("{.reg .pred p; setp.ne.b32 p, %65, 0;\n"
  "wgmma.mma_async.sync.aligned.m64n120k16.f32.bf16.bf16 {%0,%1,%2,%3,%4,%5,%6,%7,%8,%9,%10,%11,%12,%13,%14,%15,%16,%17,%18,%19,%20,%21,%22,%23,%24,%25,%26,%27,%28,%29,%30,%31,%32,%33,%34,%35,%36,%37,%38,%39,%40,%41,%42,%43,%44,%45,%46,%47,%48,%49,%50,%51,%52,%53,%54,%55,%56,%57,%58,%59}, {%60,%61,%62,%63}, %64, p, 1, 1, 0;}\n"
  : "+f"(d[0]),"+f"(d[1]),"+f"(d[2]),"+f"(d[3]),"+f"(d[4]),"+f"(d[5]),"+f"(d[6]),"+f"(d[7]),"+f"(d[8]),"+f"(d[9]),"+f"(d[10]),"+f"(d[11]),"+f"(d[12]),"+f"(d[13]),"+f"(d[14]),"+f"(d[15]),"+f"(d[16]),"+f"(d[17]),"+f"(d[18]),"+f"(d[19]),"+f"(d[20]),"+f"(d[21]),"+f"(d[22]),"+f"(d[23]),"+f"(d[24]),"+f"(d[25]),"+f"(d[26]),"+f"(d[27]),"+f"(d[28]),"+f"(d[29]),"+f"(d[30]),"+f"(d[31]),"+f"(d[32]),"+f"(d[33]),"+f"(d[34]),"+f"(d[35]),"+f"(d[36]),"+f"(d[37]),"+f"(d[38]),"+f"(d[39]),"+f"(d[40]),"+f"(d[41]),"+f"(d[42]),"+f"(d[43]),"+f"(d[44]),"+f"(d[45]),"+f"(d[46]),"+f"(d[47]),"+f"(d[48]),"+f"(d[49]),"+f"(d[50]),"+f"(d[51]),"+f"(d[52]),"+f"(d[53]),"+f"(d[54]),"+f"(d[55]),"+f"(d[56]),"+f"(d[57]),"+f"(d[58]),"+f"(d[59]) : "r"(a0),"r"(a1),"r"(a2),"r"(a3),"l"(db),"r"(sd)); } };
template<> struct WRS<128>{ static __device__ __forceinline__ void f(float* d, uint32_t a0, uint32_t a1, uint32_t a2, uint32_t a3, uint64_t db, int sd){
  asm volatile("{.reg .pred p; setp.ne.b32 p, %69, 0;\n"
  "wgmma.mma_async.sync.aligned.m64n128k16.f32.bf16.bf16 {%0,%1,%2,%3,%4,%5,%6,%7,%8,%9,%10,%11,%12,%13,%14,%15,%16,%17,%18,%19,%20,%21,%22,%23,%24,%25,%26,%27,%28,%29,%30,%31,%32,%33,%34,%35,%36,%37,%38,%39,%40,%41,%42,%43,%44,%45,%46,%47,%48,%49,%50,%51,%52,%53,%54,%55,%56,%57,%58,%59,%60,%61,%62,%63}, {%64,%65,%66,%67}, %68, p, 1, 1, 0;}\n"
  : "+f"(d[0]),"+f"(d[1]),"+f"(d[2]),"+f"(d[3]),"+f"(d[4]),"+f"(d[5]),"+f"(d[6]),"+f"(d[7]),"+f"(d[8]),"+f"(d[9]),"+f"(d[10]),"+f"(d[11]),"+f"(d[12]),"+f"(d[13]),"+f"(d[14]),"+f"(d[15]),"+f"(d[16]),"+f"(d[17]),"+f"(d[18]),"+f"(d[19]),"+f"(d[20]),"+f"(d[21]),"+f"(d[22]),"+f"(d[23]),"+f"(d[24]),"+f"(d[25]),"+f"(d[26]),"+f"(d[27]),"+f"(d[28]),"+f"(d[29]),"+f"(d[30]),"+f"(d[31]),"+f"(d[32]),"+f"(d[33]),"+f"(d[34]),"+f"(d[35]),"+f"(d[36]),"+f"(d[37]),"+f"(d[38]),"+f"(d[39]),"+f"(d[40]),"+f"(d[41]),"+f"(d[42]),"+f"(d[43]),"+f"(d[44]),"+f"(d[45]),"+f"(d[46]),"+f"(d[47]),"+f"(d[48]),"+f"(d[49]),"+f"(d[50]),"+f"(d[51]),"+f"(d[52]),"+f"(d[53]),"+f"(d[54]),"+f"(d[55]),"+f"(d[56]),"+f"(d[57]),"+f"(d[58]),"+f"(d[59]),"+f"(d[60]),"+f"(d[61]),"+f"(d[62]),"+f"(d[63]) : "r"(a0),"r"(a1),"r"(a2),"r"(a3),"l"(db),"r"(sd)); } };
__device__ __forceinline__ void wgmma_ss_n128_ta1_tb1(float* d, uint32_t da, uint32_t db, int sd){
  asm volatile("{.reg .pred p; .reg .b64 a, b; setp.ne.b32 p, %66, 0; mov.b64 a, {%64, 0x40000040}; mov.b64 b, {%65, 0x40000040};\n"
  "wgmma.mma_async.sync.aligned.m64n128k16.f32.bf16.bf16 {%0,%1,%2,%3,%4,%5,%6,%7,%8,%9,%10,%11,%12,%13,%14,%15,%16,%17,%18,%19,%20,%21,%22,%23,%24,%25,%26,%27,%28,%29,%30,%31,%32,%33,%34,%35,%36,%37,%38,%39,%40,%41,%42,%43,%44,%45,%46,%47,%48,%49,%50,%51,%52,%53,%54,%55,%56,%57,%58,%59,%60,%61,%62,%63}, a, b, p, 1, 1, 1, 1;}\n"
  : "+f"(d[0]),"+f"(d[1]),"+f"(d[2]),"+f"(d[3]),"+f"(d[4]),"+f"(d[5]),"+f"(d[6]),"+f"(d[7]),"+f"(d[8]),"+f"(d[9]),"+f"(d[10]),"+f"(d[11]),"+f"(d[12]),"+f"(d[13]),"+f"(d[14]),"+f"(d[15]),"+f"(d[16]),"+f"(d[17]),"+f"(d[18]),"+f"(d[19]),"+f"(d[20]),"+f"(d[21]),"+f"(d[22]),"+f"(d[23]),"+f"(d[24]),"+f"(d[25]),"+f"(d[26]),"+f"(d[27]),"+f"(d[28]),"+f"(d[29]),"+f"(d[30]),"+f"(d[31]),"+f"(d[32]),"+f"(d[33]),"+f"(d[34]),"+f"(d[35]),"+f"(d[36]),"+f"(d[37]),"+f"(d[38]),"+f"(d[39]),"+f"(d[40]),"+f"(d[41]),"+f"(d[42]),"+f"(d[43]),"+f"(d[44]),"+f"(d[45]),"+f"(d[46]),"+f"(d[47]),"+f"(d[48]),"+f"(d[49]),"+f"(d[50]),"+f"(d[51]),"+f"(d[52]),"+f"(d[53]),"+f"(d[54]),"+f"(d[55]),"+f"(d[56]),"+f"(d[57]),"+f"(d[58]),"+f"(d[59]),"+f"(d[60]),"+f"(d[61]),"+f"(d[62]),"+f"(d[63]) : "r"(da),"r"(db),"r"(sd)); }
__device__ __forceinline__ void wgmma_ss_n80_ta0_tb1(float* d, uint32_t da, uint32_t db, int sd){
  asm volatile("{.reg .pred p; .reg .b64 a, b; setp.ne.b32 p, %42, 0; mov.b64 a, {%40, 0x40}; mov.b64 b, {%41, 0x8};\n"
  "wgmma.mma_async.sync.aligned.m64n80k16.f32.bf16.bf16 {%0,%1,%2,%3,%4,%5,%6,%7,%8,%9,%10,%11,%12,%13,%14,%15,%16,%17,%18,%19,%20,%21,%22,%23,%24,%25,%26,%27,%28,%29,%30,%31,%32,%33,%34,%35,%36,%37,%38,%39}, a, b, p, 1, 1, 0, 1;}\n"
  : "+f"(d[0]),"+f"(d[1]),"+f"(d[2]),"+f"(d[3]),"+f"(d[4]),"+f"(d[5]),"+f"(d[6]),"+f"(d[7]),"+f"(d[8]),"+f"(d[9]),"+f"(d[10]),"+f"(d[11]),"+f"(d[12]),"+f"(d[13]),"+f"(d[14]),"+f"(d[15]),"+f"(d[16]),"+f"(d[17]),"+f"(d[18]),"+f"(d[19]),"+f"(d[20]),"+f"(d[21]),"+f"(d[22]),"+f"(d[23]),"+f"(d[24]),"+f"(d[25]),"+f"(d[26]),"+f"(d[27]),"+f"(d[28]),"+f"(d[29]),"+f"(d[30]),"+f"(d[31]),"+f"(d[32]),"+f"(d[33]),"+f"(d[34]),"+f"(d[35]),"+f"(d[36]),"+f"(d[37]),"+f"(d[38]),"+f"(d[39]) : "r"(da),"r"(db),"r"(sd)); }
__device__ __forceinline__ void wgmma_ss_n160_ta0_tb1(float* d, uint32_t da, uint32_t db, int sd){
  asm volatile("{.reg .pred p; .reg .b64 a, b; setp.ne.b32 p, %82, 0; mov.b64 a, {%80, 0x40}; mov.b64 b, {%81, 0x8};\n"
  "wgmma.mma_async.sync.aligned.m64n160k16.f32.bf16.bf16 {%0,%1,%2,%3,%4,%5,%6,%7,%8,%9,%10,%11,%12,%13,%14,%15,%16,%17,%18,%19,%20,%21,%22,%23,%24,%25,%26,%27,%28,%29,%30,%31,%32,%33,%34,%35,%36,%37,%38,%39,%40,%41,%42,%43,%44,%45,%46,%47,%48,%49,%50,%51,%52,%53,%54,%55,%56,%57,%58,%59,%60,%61,%62,%63,%64,%65,%66,%67,%68,%69,%70,%71,%72,%73,%74,%75,%76,%77,%78,%79}, a, b, p, 1, 1, 0, 1;}\n"
  : "+f"(d[0]),"+f"(d[1]),"+f"(d[2]),"+f"(d[3]),"+f"(d[4]),"+f"(d[5]),"+f"(d[6]),"+f"(d[7]),"+f"(d[8]),"+f"(d[9]),"+f"(d[10]),"+f"(d[11]),"+f"(d[12]),"+f"(d[13]),"+f"(d[14]),"+f"(d[15]),"+f"(d[16]),"+f"(d[17]),"+f"(d[18]),"+f"(d[19]),"+f"(d[20]),"+f"(d[21]),"+f"(d[22]),"+f"(d[23]),"+f"(d[24]),"+f"(d[25]),"+f"(d[26]),"+f"(d[27]),"+f"(d[28]),"+f"(d[29]),"+f"(d[30]),"+f"(d[31]),"+f"(d[32]),"+f"(d[33]),"+f"(d[34]),"+f"(d[35]),"+f"(d[36]),"+f"(d[37]),"+f"(d[38]),"+f"(d[39]),"+f"(d[40]),"+f"(d[41]),"+f"(d[42]),"+f"(d[43]),"+f"(d[44]),"+f"(d[45]),"+f"(d[46]),"+f"(d[47]),"+f"(d[48]),"+f"(d[49]),"+f"(d[50]),"+f"(d[51]),"+f"(d[52]),"+f"(d[53]),"+f"(d[54]),"+f"(d[55]),"+f"(d[56]),"+f"(d[57]),"+f"(d[58]),"+f"(d[59]),"+f"(d[60]),"+f"(d[61]),"+f"(d[62]),"+f"(d[63]),"+f"(d[64]),"+f"(d[65]),"+f"(d[66]),"+f"(d[67]),"+f"(d[68]),"+f"(d[69]),"+f"(d[70]),"+f"(d[71]),"+f"(d[72]),"+f"(d[73]),"+f"(d[74]),"+f"(d[75]),"+f"(d[76]),"+f"(d[77]),"+f"(d[78]),"+f"(d[79]) : "r"(da),"r"(db),"r"(sd)); }

struct Strm { uint32_t n0, n1; };
struct AW { uint32_t c0, n0, c1, n1; };
struct ConvCtx { uint32_t sb, ea, eb, ec, ed, pa, pc, z; uint64_t da, db, dc; bool l0; };
__host__ __device__ constexpr int st_S(int n) { return n < 34 ? ((n & 1) ? 2 : 0) : 1; }
__host__ __device__ constexpr int st_I(int n) { return n < 34 ? n / 2 : n - 34; }
template <int N>
__device__ __forceinline__ void load_aw(AW& w, const ConvCtx& x) {
  constexpr int S = st_S(N), I = st_I(N);
  constexpr uint32_t o = (S == 1 ? 2 * ECH : 0) + 2 * I * REC;
  if (S == 0) mbar_wait_u(x.sb + B_ERDY + 8 * I, 0);
  const uint32_t ea = S == 2 ? x.ec : x.ea, eb = S == 2 ? x.ed : x.eb;
  w.c0 = lds32(ea + o); w.c1 = lds32(eb + o); w.n0 = lds32(ea + o + REC); w.n1 = lds32(eb + o + REC);
}
template <int N> struct Step {
  static __device__ __forceinline__ void run(float* a, float* b, float* c, Strm* st, AW& w, const ConvCtx& x) {
    constexpr int S = st_S(N), I = st_I(N), HALF = S == 2, J = (I > 0) ? I - 1 : 0;
    float* acc = S == 0 ? a : (S == 1 ? b : c);
    if (N == 34) mbar_wait_u(x.sb + B_KFL, 0);
    if (N == 34) mbar_wait_u(x.sb + B_EDONE, 0);
    if (I > 0) wg_wait<(N < 33) ? 1 : 0>();
    constexpr bool dump = (I > 0) && (!HALF || (I & 1) == 0);
    constexpr int DS = HALF ? (J / 2) : J;
    if (I < 16) {
      constexpr int F = HALF ? ((I & 15) / 2) : (I & 15);
      constexpr int NR = HALF ? 32 : 64;
      if (dump) {
#pragma unroll
        for (int r = 4 * F; r < NR; r++) { float nv; asm volatile("mov.f32 %0, %1;" : "=f"(nv) : "f"(acc[r])); acc[r] = nv; }
      }
      uint32_t c0 = w.c0, n0 = w.n0, c1 = w.c1, n1 = w.n1, p0, p1, e0, e1;
      if (I > 0) {
        const uint32_t dep = __float_as_uint(acc[dump ? 4 * DS : 4 * F]);
        p0 = xz(st[S].n0, x.z); p1 = xz(st[S].n1, x.z); e0 = xz3(c0, dep, x.z); e1 = xz3(c1, dep, x.z);
      } else { p0 = xz3(x.z, c0, x.z); p1 = xz3(x.z, c1, x.z); e0 = xz(c0, x.z); e1 = xz(c1, x.z); }
      if (N < 49) load_aw<N == 31 ? 34 : (N < 49 ? N + 1 : 0)>(w, x);
      asm volatile("wgmma.fence.sync.aligned;" : "+r"(p0), "+r"(p1), "+r"(e0), "+r"(e1), "+r"(c0), "+r"(c1), "+r"(n0), "+r"(n1)::"memory");
      const uint64_t d = (S == 0 ? x.da : (S == 1 ? x.db : x.dc)) - (HALF ? (I & 1) * 16 : 0);
      WRS<2 * NR - 8 * F>::f(acc + 4 * F, c0, n0, p0, e0, d, I > 0);
      WRS<2 * NR - 8 * F>::f(acc + 4 * F, c1, n1, p1, e1, d - 1, 1);
      st[S].n0 = n0; st[S].n1 = n1;
      wg_commit();
    }
    if (dump) stsm2t((HALF ? x.pc : x.pa) + (HALF ? 2 * DS : DS) * 256, packbf(acc[4 * DS], acc[4 * DS + 1]), packbf(acc[4 * DS + 2], acc[4 * DS + 3]));
    if (S != 0 && I >= 4 && (I & (S == 1 ? 7 : 3)) == 0) { fence_async_s(); __syncwarp(); if (x.l0) mbar_arrive(x.sb + B_YRDY + 2 * (I >= 4 ? I - 4 : 0)); }
    if (S != 0 && (I & 3) == 0) STAMP0(72 + I / 4 + (S == 1 ? 5 : 0));
    Step<N + 1>::run(a, b, c, st, w, x);
  }
};
template <> struct Step<51> { static __device__ __forceinline__ void run(float*, float*, float*, Strm*, AW&, const ConvCtx&) {} };

struct EpiCtx { float n0, n1, m0, m1; uint32_t cs; unsigned char* gp; };
__device__ __forceinline__ float swiglu(float ag, float au, float mu, float n, float cg, float cu) {
  const float dg = fmaf(-mu, cg, ag), du = fmaf(-mu, cu, au);
  float t; asm("tanh.approx.f32 %0, %1;" : "=f"(t) : "f"(dg * n));
  const float p = dg * du;
  return fmaf(p, t, p);
}
template <int P, int J>
__device__ __forceinline__ void epi_piece(const float* acc, const EpiCtx& e, float4 c) {
  const float g0 = swiglu(acc[4 * J], acc[32 + 4 * J], e.m0, e.n0, c.x, c.z);
  const float g1 = swiglu(acc[4 * J + 1], acc[33 + 4 * J], e.m0, e.n0, c.y, c.w);
  const float g2 = swiglu(acc[4 * J + 2], acc[34 + 4 * J], e.m1, e.n1, c.x, c.z);
  const float g3 = swiglu(acc[4 * J + 3], acc[35 + 4 * J], e.m1, e.n1, c.y, c.w);
  *reinterpret_cast<uint32_t*>(e.gp + P * 16384 + J * 128) = packbf(g0, g1);
  *reinterpret_cast<uint32_t*>(e.gp + P * 16384 + J * 128 + 1024) = packbf(g2, g3);
}
__host__ __device__ constexpr int pieces_before(int p, int kb) {
  return p == 1 ? (kb < P1K0 ? 0 : (kb >= 10 ? 8 : kb - P1K0 + (P1K0 > 2 && kb > P1K0 + 1) + (P1K0 > 3 && kb > P1K0 + 3))) : (kb < 1 ? 0 : (kb - 1 + (kb > P2D0) + (kb > P2D1) > 8 ? 8 : kb - 1 + (kb > P2D0) + (kb > P2D1)));
}
template <int P, int KB> struct G1 {
  static __device__ __forceinline__ void run(float* cur, const float* prev, uint32_t sb, uint32_t da, uint32_t dw, bool l0, EpiCtx& e, uint32_t st2, float4 c, float4 c2, float4* cs2) {
    constexpr int s = P * 10 + KB;
    mbar_wait_u(sb + B_WFULL + 8 * (s & 3), (s >> 2) & 1);
    wg_fence();
#pragma unroll
    for (int k = 0; k < 4; k++) wgmma_ss_n128_ta1_tb1(cur, da + KB * 1024 + k * 128, dw + (s & 3) * 1024 + k * 128, (KB > 0 || k > 0));
    wg_commit();
    constexpr int J0 = pieces_before(P, KB), J1 = pieces_before(P, KB + 1), J2 = pieces_before(P, KB + 2);
    if (J1 == 0 && J2 > 0) {
      if (P == 1) {
        mbar_wait_u(sb + B_S2, 0);
        const float2 a = lds64f(st2), b = lds64f(st2 + 64);
        e.n0 = a.x * NSCALE; e.m0 = a.y; e.n1 = b.x * NSCALE; e.m1 = b.y;
      }
      mbar_wait_u(sb + B_CS + 8 * (P - 1), 0);
    }
    wg_wait<1>();
    if (l0) { mbar_arrive(sb + B_WEMPTY + 8 * ((s + 3) & 3)); if (P == 2 && KB > 0) mbar_arrive(sb + B_AEMPTY + 8 * (KB > 0 ? KB - 1 : 0)); }
    if (J1 > J0) c = lds128f(e.cs + (P - 1) * 512 + (J0 & 7) * 64);
    if (J1 > J0 + 1) c2 = lds128f(e.cs + (P - 1) * 512 + ((J0 + 1) & 7) * 64);
    float4 cn = c, cn2 = c;
    if (!RELFIRST && J2 > J1) cn = lds128f(e.cs + (P - 1) * 512 + (J1 & 7) * 64);
    if (!RELFIRST && J2 > J1 + 1) cn2 = lds128f(e.cs + (P - 1) * 512 + ((J1 + 1) & 7) * 64);
    if (J1 > J0) epi_piece<P - 1, J0 & 7>(prev, e, c);
    if (J1 > J0 + 1) epi_piece<P - 1, (J0 + 1) & 7>(prev, e, c2);
    if (P == 2 && KB == 2) mbar_wait_u(sb + B_CS + 16, 0);
    if (P == 2 && KB >= 2) cs2[(KB + 6) & 7] = lds128f(e.cs + 1024 + ((KB + 6) & 7) * 64);
    if (J1 == 8 && J0 < 8) bar_arrive(3 + P - 1, P == 1 ? 320 : 288);
    if (G2STAMP) STAMP0(90 + 10 * P + KB);
    G1<P, KB + 1>::run(cur, prev, sb, da, dw, l0, e, st2, cn, cn2, cs2);
  }
};
template <int P> struct G1<P, 10> { static __device__ __forceinline__ void run(float*, const float*, uint32_t, uint32_t, uint32_t, bool, EpiCtx&, uint32_t, float4, float4, float4*) {} };

__host__ __device__ constexpr int g2_slot(int t) { return t < 32 ? t / 3 : (t + 32) / 6; }
__host__ __device__ constexpr int g2_blk(int t) { return t < 32 ? t / 4 : 8 + ((t - 32) & 15) / 4; }
__host__ __device__ constexpr int w2_buf(int s) { return (s % 6) < 4 ? 2 + (((s % 6) + 2) & 3) : (s % 6) - 4; }
__host__ __device__ constexpr uint32_t w2_full(int s) { return w2_buf(s) < 2 ? B_AFULL + 64 + 8 * w2_buf(s) : B_WFULL + 8 * (w2_buf(s) - 2); }
__host__ __device__ constexpr uint32_t w2_empty(int s) { return w2_buf(s) < 2 ? B_AEMPTY + 64 + 8 * w2_buf(s) : B_WEMPTY + 8 * (w2_buf(s) - 2); }
__host__ __device__ constexpr uint32_t w2_fpar(int s) { return ((s / 6) + ((s % 6) < 2 ? 1 : 0)) & 1; }
template <int T0, int T1>
__device__ __forceinline__ void g2_issue(float* o, uint32_t sb, uint32_t dg, uint32_t dwa, uint32_t dwb) {
#pragma unroll
  for (int t = T0; t < T1; t++) {
    if (t < 48 && (t & 3) == 0) mbar_wait_u(sb + B_AFULL + 8 * (g2_blk(t) & 7), g2_blk(t) >> 3);
    if (t == 0 || g2_slot(t) != g2_slot(t - 1)) mbar_wait_u(sb + w2_full(g2_slot(t)), w2_fpar(g2_slot(t)));
  }
  wg_fence();
#pragma unroll
  for (int t = T0; t < T1; t++) {
    const uint32_t a = dg + (g2_blk(t) & 7) * 1024 + (t & 3) * 16, w = w2_buf(g2_slot(t)) * 1024;
    if (t < 32) wgmma_ss_n160_ta0_tb1(o, a, dwa + w + (t % 3) * 320, t > 0);
    else wgmma_ss_n80_ta0_tb1(o + (t < 48 ? 0 : 40), a, dwb + w + ((t + 32) % 6) * 160, 1);
  }
  wg_commit();
}
template <int T0, int T1>
__device__ __forceinline__ void g2_release(uint32_t sb, bool l0) {
  if (l0) {
#pragma unroll
    for (int t = T0; t < T1; t++) {
      if (g2_slot(t) != g2_slot(t + 1) && g2_slot(t) < 10) mbar_arrive(sb + w2_empty(g2_slot(t)));
      if ((t < 16 && (t & 3) == 3) || t == 31) mbar_arrive(sb + B_AEMPTY + 8 * (t >> 2));
    }
  }
}
template <int T, int TE, int G> struct G2 {
  static __device__ __forceinline__ void run(float* o, uint32_t sb, uint32_t dg, uint32_t dwa, uint32_t dwb, bool l0) {
    g2_issue<T, T + G>(o, sb, dg, dwa, dwb);
    wg_wait<1>();
    g2_release<T - G, T>(sb, l0);
    G2<T + G, TE, G>::run(o, sb, dg, dwa, dwb, l0);
  }
};
template <int TE, int G> struct G2<TE, TE, G> { static __device__ __forceinline__ void run(float*, uint32_t, uint32_t, uint32_t, uint32_t, bool) {} };

__device__ __forceinline__ void wgmma_ss_n8(float* d, uint32_t da, uint32_t db, int sd) {
  asm volatile("{.reg .pred p; .reg .b64 a, b; setp.ne.b32 p, %6, 0; mov.b64 a, {%4, 8}; mov.b64 b, {%5, 8};\n"
               "wgmma.mma_async.sync.aligned.m64n8k16.f32.bf16.bf16 {%0,%1,%2,%3}, a, b, p, 1, 1, 0, 0;}\n"
               : "+f"(d[0]), "+f"(d[1]), "+f"(d[2]), "+f"(d[3]) : "r"(da), "r"(db), "r"(sd));
}
__device__ __forceinline__ void wgmma_ss_n8_ta(float* d, uint64_t da, uint64_t db) {
  asm volatile("{.reg .pred p; setp.eq.b32 p, 0, 0;\nwgmma.mma_async.sync.aligned.m64n8k16.f32.bf16.bf16 {%0,%1,%2,%3}, %4, %5, p, 1, 1, 1, 0;}\n"
               : "+f"(d[0]), "+f"(d[1]), "+f"(d[2]), "+f"(d[3]) : "l"(da), "l"(db));
}
__device__ __forceinline__ void ld_stats(float4& sa, float4& sc, const float2* p) {
  asm volatile("ld.relaxed.gpu.global.v4.f32 {%0,%1,%2,%3}, [%4];" : "=f"(sa.x), "=f"(sa.y), "=f"(sa.z), "=f"(sa.w) : "l"(p) : "memory");
  asm volatile("ld.relaxed.gpu.global.v4.f32 {%0,%1,%2,%3}, [%4];" : "=f"(sc.x), "=f"(sc.y), "=f"(sc.z), "=f"(sc.w) : "l"(p + 64) : "memory");
}
__device__ __forceinline__ void check_stats(float4& a, float4& c, const float2* p, uint32_t tag) {
  unsigned n = 0;
  while (!__all_sync(0xffffffff, (((__float_as_uint(a.x) ^ tag) | (__float_as_uint(a.z) ^ tag) | (__float_as_uint(c.x) ^ tag) | (__float_as_uint(c.z) ^ tag)) & 3) == 0)) {
    SPIN_GUARD(n); __nanosleep(100); ld_stats(a, c, p);
  }
}
__device__ __forceinline__ void red_sum(float* y, uint32_t da, uint32_t db) {
  wgmma_ss_n8(y, da, db, 0);
  wgmma_ss_n8(y, da + (2 * PR - 64) / 16, db, 1);
}
__device__ __forceinline__ void red_fin(uint32_t* hp, const float* y, uint32_t xl, uint32_t xh, const float4& sa, const float4& sc) {
  const float x0 = bflo(xl), x1 = bfhi(xl), x2 = bflo(xh), x3 = bfhi(xh);
  hp[0] = packbf(x0 + (x0 * sa.x - sa.y) * y[0], x1 + (x1 * sa.z - sa.w) * y[1]);
  hp[32] = packbf(x2 + (x2 * sc.x - sc.y) * y[2], x3 + (x3 * sc.z - sc.w) * y[3]);
}
__device__ __forceinline__ void fetch_colsum(uint32_t sb, int f, int p, int lane, unsigned tag) {
  const void* src = g_colsum + (f * 3 + p) * 128 + lane * 4;
  uint4 u; unsigned c = 0;
  for (;;) {
    asm volatile("ld.relaxed.gpu.global.v4.u32 {%0,%1,%2,%3}, [%4];" : "=r"(u.x), "=r"(u.y), "=r"(u.z), "=r"(u.w) : "l"(src) : "memory");
    if (__all_sync(0xffffffff, (((u.x ^ tag) | (u.y ^ tag) | (u.z ^ tag) | (u.w ^ tag)) & 3) == 0)) break;
    SPIN_GUARD(c);
    __nanosleep(200);
  }
  sts128(sb + OFF_CS + p * 512 + lane * 16, u);
  __syncwarp();
  if (lane == 0) mbar_arrive(sb + B_CS + 8 * p);
  STAMP(29 + p);
}
__device__ __forceinline__ uint32_t eoff(uint32_t i) { const uint32_t q = (i >> 2) & 3; return (4 * q + ((i >> 4) ^ (q & 2))) * 16 + (i & 3) * 4; }
__device__ __forceinline__ int logical_id() {
  int cta; asm volatile("mov.u32 %0, %%ctaid.x;" : "=r"(cta));
  const int c = cta >> 1, q7 = ((c - 36) * 37) >> 8;
  const int m = c < 4 ? 15 : (c < 36 ? (c - 4) & 7 : c - 28 - 7 * q7), qi = c < 4 ? c : (c < 36 ? (c - 4) >> 3 : q7);
  return 8 * m + 2 * qi + (cta & 1);
}

struct Maps { CUtensorMap h, hr, w1, w3, w2, c[2][5]; };
struct Params {
  const __nv_bfloat16 *kf, *k, *v, *x, *shift, *D, *w2;
  __nv_bfloat16* out;
  uint32_t z;
};

__device__ __forceinline__ void patch_tap0(uint32_t sb, uint32_t off, int c0, int n, uint32_t bin, uint32_t bout, int lane) {
  const int lid = logical_id();
  mbar_wait(sb + bin, 0);
  if (lane < n) {
    const uint32_t a = sb + off + lane * KS, k0 = lds32(a), i = 5 * lid + c0 + lane - ((5 * (lid & ~1)) & ~7);
    const uint32_t dw = lds32(sb + OFF_D + (i >> 1) * 4);
    sts32(a, prmt(packbf(bflo(k0) + ((i & 1) ? bfhi(dw) : bflo(dw)), 0.f), k0, 0x7610));
  }
  fence_async_s();
  __syncwarp();
  if (lane == 0) mbar_arrive(sb + bout);
}
__device__ __forceinline__ void issue_task(const Maps& tm, uint32_t sb, int lid, int n, uint32_t sl) {
  const int G0 = (5 * (lid & ~1)) >> 3;
  const bool wide = (G0 & 3) != 3;
  const CUtensorMap* mp = tm.c[wide ? 1 : 0];
  const uint32_t d = sb + slot_off(sl), b = sb + B_TFULL + 8 * sl;
  const int c0 = (wide ? (G0 & ~3) : G0) * 8, t0 = 16 * n + 8 * (lid & 1);
  tma4d(d, mp, c0, t0, 0, b);
  tma4d(d + 8192, mp + 1, c0, t0, 0, b);
  tma4d(d + 24576, mp + 3, c0, t0 - 1, 6, b);
  tma4d(d + 24832, mp + 4, c0, t0 - 1, 6, b);
  tma4d(d + 16384, mp + 2, c0, t0, 0, b);
  mbar_expect(b, wide ? 25088 : 12544);
}

__global__ void __cluster_dims__(2, 1, 1) __launch_bounds__(512, 1)
h3_ffn_kernel(const __grid_constant__ Params pr, const __grid_constant__ Maps tm) {
  extern __shared__ __align__(1024) unsigned char smem[];
  STAMP0(127);
  if (threadIdx.x == 480 && blockIdx.x < 128) {
    prefetch_l2(pr.k + blockIdx.x * 1280, 2560); prefetch_l2(pr.v + blockIdx.x * 1280, 2560);
    prefetch_l2(pr.kf + blockIdx.x * 10240, 12288); prefetch_l2(pr.x + blockIdx.x * 1280, 2560);
    prefetch_l2(pr.k + 163840 + blockIdx.x * 1280, 2560); prefetch_l2(pr.v + 163840 + blockIdx.x * 1280, 2560);
    prefetch_l2(pr.x + 163840 + blockIdx.x * 1280, 2560);
  }
  const uint32_t sb = (uint32_t)__cvta_generic_to_shared(smem);
  const int wsel = __shfl_sync(0xffffffff, threadIdx.x >> 5, 0), wgsel = wsel >> 2;
  const int cta = blockIdx.x;
  if (cta < 128) {
    {
      if (wsel == 0) {
        const int lid = logical_id();
        if (elect1()) {
          mbar_init(sb + B_TFULL + 8, 1); mbar_init(sb + B_TFULL + 16, 1);
          mbar_init(sb + B_KF0, 1); mbar_init(sb + B_KF0 + 8, 1); mbar_init(sb + B_KF, 1);
#pragma unroll 1
          for (int n = 0; n < 2; n++) {
            if (n == ((((5 * (lid & ~1)) >> 3) & 3) == 3 ? KFPOSH : KFPOS)) {
              const int G8 = (5 * (lid & ~1)) & ~7;
              bulk_g2s(sb + OFF_SH, pr.shift + 4 * G8, 128, sb + B_KF0 + 8);
              bulk_g2s(sb + OFF_D, pr.D + G8, 32, sb + B_KF0);
#pragma unroll
              for (int c = 0; c < 3; c++) bulk_g2s(sb + OFF_KFE + c * KS, pr.kf + (5 * lid + c) * 2048, 4096, sb + B_KF0);
              mbar_expect(sb + B_KF0 + 8, 128);
              mbar_expect(sb + B_KF0, 3 * 4096 + 32);
            }
            issue_task(tm, sb, lid, n, 1 + n);
          }
        }
        __syncwarp();
        STAMP(13);
      }
      if (wsel == 1 && elect1()) {
#pragma unroll
        for (int i = 0; i < 16; i++) mbar_init(sb + B_ERDY + 8 * i, 1);
        asm volatile("fence.mbarrier_init.release.cluster;" ::: "memory");
#pragma unroll
        for (int i = 0; i < 8; i++) mbar_expect(sb + B_ERDY + 16 * i + 8 * ((cta & 1) ^ 1), 2 * REC);
      }
      if (wsel == 3 && elect1()) {
#pragma unroll
        for (int i = 0; i < 10; i++) if (i != 1 && i != 2) mbar_init(sb + B_AFULL + 8 * i, 1);
#pragma unroll
        for (int i = 0; i < 10; i++) if (i != 1 && i != 2) mbar_arrive(sb + B_AFULL + 8 * i);
      }
      if (wsel == 2 && elect1()) {
#pragma unroll
        for (int i = 0; i < 4; i++) {
          mbar_init(sb + B_YRDY + 8 * i, 8); mbar_init(sb + B_S2 + 8 * i, i ? 1 : 4);
          mbar_init(sb + B_WFULL + 8 * i, 1); mbar_init(sb + B_WEMPTY + 8 * i, 8);
        }
#pragma unroll
        for (int i = 0; i < 10; i++) mbar_init(sb + B_AEMPTY + 8 * i, 8);
        mbar_init(sb + B_CDONE, 4); mbar_init(sb + B_EP, 1); mbar_init(sb + B_XFREE, 8); mbar_init(sb + B_XIN, 1);
        asm volatile("fence.mbarrier_init.release.cluster;" ::: "memory");
        mbar_expect(sb + B_XIN, 20480);
        mbar_init(sb + B_W2G, 4); mbar_init(sb + B_EDONE, 8); mbar_init(sb + B_KFL0, 1); mbar_init(sb + B_KFL, 1);
      }
      if (wgsel == 1) {
        const int t = threadIdx.x & 127;
        const uint4 zero = make_uint4(0, 0, 0, 0);
        if (t < 120) {
          sts128(sb + OFF_U - REC + t * 16, zero);
          if (t < 112) sts128(sb + OFF_P + (t >> 3) * PR + (t & 7) * 16, zero);
          if (t < 26) sts128(sb + OFF_KFE - 16 + (t < 24 ? -16 * t : (t - 23) * KS), zero);
          if (t < 32) sts32(sb + OFF_ID + 4 * t, (t & 3) == (t >> 3) ? (0x3f80u << (4 * (t & 4))) : 0u);
        }
        fence_async_s();
      }
      __syncwarp();
      cl_arrive_rlx();
      bar_sync(0, 512);
      STAMP0(12);
    }
  }
#define ROLE_IDS const int tid = tid_x(), lane = tid & 31, warp = __shfl_sync(0xffffffff, tid >> 5, 0), wg = warp >> 2, w4 = warp & 3; (void)wg; (void)w4; (void)lane;

  if (cta >= 128) {
    ROLE_IDS
    const uint32_t bf = sb + OFF_MISC, be = bf + 96;
    if (warp == 0 && elect1()) {
#pragma unroll
      for (int i = 0; i < 12; i++) { mbar_init(bf + 8 * i, 1); mbar_init(be + 8 * i, 4); }
    }
    if (warp == 1) { sts32(sb + OFF_MISC + 512 + 4 * lane, 0x3f803f80u); fence_async_s(); }
    const unsigned t0 = clock();
    const unsigned tag = (ld_relaxed(&g_done) / NCTA + 1) & 3;
    __syncthreads();
    if (wg < 2) {
      const int f = 2 * (cta - 128) + wg;
      const uint64_t db = mkdesc(sb + OFF_MISC + 512, 0, 128, 0);
      uint32_t sl = wg, ph = 0, rel = 0;
#pragma unroll 1
      for (int p = 0; p < 3; p++) {
        float ag[4] = {0.f, 0.f, 0.f, 0.f}, au[4] = {0.f, 0.f, 0.f, 0.f};
#pragma unroll 1
        for (int kb = 0; kb < 10; kb++) {
          mbar_wait(bf + 8 * sl, ph);
          wg_fence();
          const uint64_t dw = mkdesc(sb + sl * 16384, 8192, 1024, 1);
#pragma unroll
          for (int k = 0; k < 4; k++) { wgmma_ss_n8_ta(ag, dw + k * 128, db); wgmma_ss_n8_ta(au, dw + 512 + k * 128, db); }
          wg_commit();
          wg_wait<1>();
          if (lane == 0 && kb > 0) mbar_arrive(be + 8 * rel);
          rel = sl;
          sl += 2; if (sl >= 12) { sl -= 12; ph ^= 1; }
        }
        wg_wait<0>();
        if (lane == 0) mbar_arrive(be + 8 * rel);
        const int g = lane >> 2, t = lane & 3;
        const float v = (t & 1) ? ((t & 2) ? au[2] : au[0]) : ((t & 2) ? ag[2] : ag[0]);
        st_relaxed(reinterpret_cast<unsigned*>(g_colsum) + (f * 3 + p) * 128 + 16 * (2 * w4 + (t >> 1)) + 4 * (g >> 1) + 2 * (t & 1) + (g & 1),
                   (__float_as_uint(v) & ~3u) | tag);
      }
    } else if (warp == 10) {
      if (elect1()) {
        while ((int)(clock() - t0) < W2PF_DELAY) {}
#pragma unroll 1
        for (int i = 0; i < (W2PF_DELAY ? 30 : 0); i++) prefetch_l2((const unsigned char*)pr.w2 + ((cta - 128) * 30 + i) * 16384, 16384);
      }
    } else if (warp < 10) {
      if (elect1()) {
        while ((int)(clock() - t0) < AUX_DELAY) {}
        uint32_t sl = w4, ph = 1;
        int c0 = 192 * (2 * (cta - 128) + w4), r0 = 0;
#pragma unroll 1
        for (int s = 0; s < 30; s++) {
          mbar_wait(be + 8 * sl, ph);
          tma3d(sb + sl * 16384, &tm.w1, c0, r0, bf + 8 * sl);
          tma3d(sb + sl * 16384 + 8192, &tm.w3, c0, r0, bf + 8 * sl);
          mbar_expect(bf + 8 * sl, 16384);
          sl += 2; if (sl >= 12) { sl -= 12; ph ^= 1; }
          if (++r0 == 10) { r0 = 0; c0 += 64; }
        }
      }
    }
    __syncthreads();
    STAMP0(0);
    if (tid == 0) red_add(&g_done, 1);
    return;
  }

  if (wgsel < 2) {
    ROLE_IDS
    asm volatile("setmaxnreg.inc.sync.aligned.u32 %0;" ::"n"(CR));
    cl_wait();
    STAMP0(10);
    {
      float a[64], b[64], c[32];
      Strm st[3];
      ConvCtx x;
      const int g = lane >> 2, t = lane & 3;
      x.sb = sb; x.z = pr.z; x.l0 = lane == 0;
      const int i0 = 16 * w4 + g - 2 * t;
      x.ec = sb + OFF_U + (i0 < 0 ? -(int)REC : 0) + eoff(i0 & 63); x.ed = sb + OFF_U + eoff(i0 + 8);
      x.ea = x.ec + (1 + wg) * ECH; x.eb = x.ed + (1 + wg) * ECH;
      x.pa = sb + OFF_P + (4 + warp) * PR + 128 + 16 * (lane & 15);
      x.pc = sb + OFF_P + w4 * PR + 128 + wg * 256 + 16 * (lane & 15);
      x.da = mkdesc(sb + OFF_KFE + (1 + wg) * KS, 128, 256, 0);
      x.db = mkdesc(sb + OFF_KFL + wg * KS, 128, 256, 0);
      x.dc = mkdesc(sb + OFF_KFE + wg * 256, 128, 512, 0);
      if (warp == 7) patch_tap0(sb, OFF_KFE, 0, 3, B_KF0, B_KF, lane);
      mbar_wait(sb + B_KF, 0);
      if (MSTART) mbar_wait(sb + B_ERDY + 8 * MSTART, 0);
      STAMP0(1);
      AW aw;
      load_aw<0>(aw, x);
      Step<0>::run(a, b, c, st, aw, x);
      STAMP0(2);
    }
    const int tid2 = tid_x(), ln = tid2 & 31;
    const int wp = __shfl_sync(0xffffffff, tid2 >> 5, 0), wgi = wp >> 2, wq = wp & 3;
    const bool l0 = ln == 0;
    const int lid = logical_id(), m = TILE_M(lid), f = TILE_F(lid);
    EpiCtx e;
    e.cs = sb + OFF_CS + (ln & 3) * 16;
    e.gp = g_g + (size_t)(m * 24 + 3 * f) * 16384 + wp * 2048 + ln * 4;
    const uint32_t st2 = sb + OFF_ST2 + (wp * 16 + (ln >> 2)) * 8;
    const uint32_t da = (uint32_t)mkdesc(sb + OFF_A + wgi * 8192, 8192, 1024, 1), dw = (uint32_t)mkdesc(sb + OFF_W, 8192, 1024, 1);
    float acc0[64], acc1[64];
#pragma unroll
    for (int i = 0; i < 64; i++) acc0[i] = 0.f;
#pragma unroll 1
    for (int kb = 0; kb < 10; kb++) {
      mbar_wait_u(sb + B_AFULL + 8 * kb, 1);
      mbar_wait_u(sb + B_WFULL + 8 * (kb & 3), (kb >> 2) & 1);
      if (kb == 0) STAMP0(3);
      wg_fence();
#pragma unroll
      for (int k = 0; k < 4; k++) wgmma_ss_n128_ta1_tb1(acc0, da + kb * 1024 + k * 128, dw + (kb & 3) * 1024 + k * 128, 1);
      wg_commit();
      wg_wait<1>();
      if (l0 && kb > 0) mbar_arrive(sb + B_WEMPTY + 8 * ((kb - 1) & 3));
      if (G2STAMP) STAMP0(84 + kb);
    }
    STAMP0(4);
    if (CR < 216) asm volatile("setmaxnreg.inc.sync.aligned.u32 216;");
    float4 cs2[8];
    G1<1, 0>::run(acc1, acc0, sb, da, dw, l0, e, st2, make_float4(0.f, 0.f, 0.f, 0.f), make_float4(0.f, 0.f, 0.f, 0.f), cs2);
    STAMP0(5);
    float acc2[64];
    G1<2, 0>::run(acc2, acc1, sb, da, dw, l0, e, st2, make_float4(0.f, 0.f, 0.f, 0.f), make_float4(0.f, 0.f, 0.f, 0.f), cs2);
    STAMP0(6);
    float o[80];
    const uint32_t dg = da ^ ((uint32_t)mkdesc(0, 8192, 0, 0) ^ (uint32_t)mkdesc(0, 128, 0, 0));
    const uint32_t dwa = (uint32_t)mkdesc(sb + OFF_W - 32768, 2560, 128, 0), dwb = (uint32_t)mkdesc(sb + OFF_W - 32768, 1280, 128, 0);
    g2_issue<0, 3>(o, sb, dg, dwa, dwb);
    wg_wait<1>();
    if (l0) { mbar_arrive(sb + B_WEMPTY + 8 * 1); mbar_arrive(sb + B_AEMPTY + 8 * 9); }
    g2_issue<3, 6>(o, sb, dg, dwa, dwb);
    STAMP0(96);
    epi_piece<2, 0>(acc2, e, cs2[0]); epi_piece<2, 1>(acc2, e, cs2[1]); epi_piece<2, 2>(acc2, e, cs2[2]); epi_piece<2, 3>(acc2, e, cs2[3]);
    wg_wait<1>();
    g2_release<0, 3>(sb, l0);
    g2_issue<6, 9>(o, sb, dg, dwa, dwb);
    epi_piece<2, 4>(acc2, e, cs2[4]); epi_piece<2, 5>(acc2, e, cs2[5]); epi_piece<2, 6>(acc2, e, cs2[6]); epi_piece<2, 7>(acc2, e, cs2[7]);
    bar_arrive(5, 288);
    STAMP0(7);
    wg_wait<1>();
    g2_release<3, 6>(sb, l0);
    G2<9, 30, 3>::run(o, sb, dg, dwa, dwb, l0);
    const uint32_t peer = mapa(sb, (logical_id() & 1) ^ 1);
    if (l0) asm volatile("mbarrier.arrive.relaxed.cluster.shared::cluster.b64 _, [%0];" ::"r"(peer + B_XFREE) : "memory");
    g2_issue<30, 32>(o, sb, dg, dwa, dwb);
    wg_wait<0>();
    g2_release<27, 32>(sb, l0);
    STAMP0(97);
#pragma unroll
    for (int r = 0; r < 80; r++) { float nv; asm volatile("mov.f32 %0, %1;" : "=f"(nv) : "f"(o[r])); o[r] = nv; }
    g2_issue<32, 36>(o, sb, dg, dwa, dwb);
    G2<36, 52, 4>::run(o, sb, dg, dwa, dwb, l0);
    STAMP0(98);
    g2_issue<52, 56>(o, sb, dg, dwa, dwb);
    {
      const int t4 = tid_x();
      const uint32_t xd = peer + OFF_A + 4 * 16384 + (t4 >> 5) * 2560 + (t4 & 31) * 16;
      mbar_wait_u(sb + B_XFREE, 0);
#pragma unroll
      for (int j = 0; j < 5; j++)
        st_async4(xd + j * 512, packbf(o[8 * j], o[8 * j + 1]), packbf(o[8 * j + 2], o[8 * j + 3]), packbf(o[8 * j + 4], o[8 * j + 5]),
                  packbf(o[8 * j + 6], o[8 * j + 7]), peer + B_XIN);
    }
    g2_issue<56, 64>(o, sb, dg, dwa, dwb);
    uint4 xin[5];
    const int t5 = tid_x(), lid5 = logical_id();
    uint32_t hres[20];
    mbar_wait_u(sb + B_AFULL + 56, 1);
#pragma unroll
    for (int j = 0; j < 5; j++)
      ldsm4t(sb + OFF_A + 4 * 16384 + 20480 + (t5 >> 7) * 10240 + (16 * j + ((t5 >> 1) & 8) + (t5 & 7)) * 128 + (((((t5 >> 4) & 6) + ((t5 >> 3) & 1)) ^ (t5 & 7)) << 4),
             hres[4 * j], hres[4 * j + 1], hres[4 * j + 2], hres[4 * j + 3]);
    mbar_wait(sb + B_XIN, 0);
#pragma unroll
    for (int j = 0; j < 5; j++) xin[j] = lds128(sb + OFF_A + 4 * 16384 + (t5 >> 5) * 2560 + (t5 & 31) * 16 + j * 512);
    wg_wait<0>();
    STAMP0(8);
    {
      const int ln = t5 & 31, wp = t5 >> 5, m = TILE_M(lid5), f = TILE_F(lid5);
      const uint32_t stg = sb + OFF_A + 4 * 16384 + 40960 + wp * 2816;
      const float r20 = e.n0 * e.n0 * RSCALE, r21 = e.n1 * e.n1 * RSCALE;
      const int mi = ln >> 3, r = ln & 7;
#pragma unroll
      for (int j = 0; j < 5; j++) {
        uint32_t v[4];
#pragma unroll
        for (int i = 0; i < 4; i++) {
          const float r2 = (i & 1) ? r21 : r20;
          const uint32_t xi = i == 0 ? xin[j].x : (i == 1 ? xin[j].y : (i == 2 ? xin[j].z : xin[j].w));
          v[i] = packbf(fmaf(o[40 + 8 * j + 2 * i] + bflo(xi), r2, bflo(hres[4 * j + i])), fmaf(o[40 + 8 * j + 2 * i + 1] + bfhi(xi), r2, bfhi(hres[4 * j + i])));
        }
        stsm4(stg + ((mi & 1) * 8 + r) * 176 + (2 * j + (mi >> 1)) * 16, v[0], v[1], v[2], v[3]);
      }
      __syncwarp();
      unsigned char* op = reinterpret_cast<unsigned char*>(pr.out + (size_t)(128 * m + 16 * wp) * 640 + 80 * f);
#pragma unroll
      for (int i = 0; i < 5; i++) {
        int idx = i * 32 + ln, row = idx / 10, c = idx - row * 10;
        stg128(op + row * 1280 + c * 16, lds128(stg + row * 176 + c * 16));
      }
    }
    STAMP0(9);
    if (t5 == 0) red_add(&g_done, 1);
  } else {
    asm volatile("setmaxnreg.dec.sync.aligned.u32 %0;" ::"n"(256 - CR));
    float4 na, nc;
    if (wgsel == 2) {
    ROLE_IDS
    {
      const int lid = logical_id(), rank = lid & 1, c10 = 5 * (lid - rank), G0 = c10 >> 3, hh = w4 & 1;
      const bool wide = (G0 & 3) != 3;
      const int lc = (G0 + hh) * 8 + (lane >> 2) - c10;
      const bool valid = (unsigned)lc < 10u;
      if (w4 == 1 && elect1()) {
        issue_task(tm, sb, lid, 2, 0);
#pragma unroll 1
        for (int n = 3; n < 3 + KVPF; n++) { prefetch_l2(pr.k + 163840 * n + lid * 1280, 2560); prefetch_l2(pr.v + 163840 * n + lid * 1280, 2560); }
      }
      __syncwarp();
      const uint32_t T = (w4 & 2) * 2 + ((lane & 7) >> 1), bb = 1 - (lane & 1), mi = lane >> 3, ch16 = wide ? (G0 & 3) + hh : hh;
      const uint32_t pitch = wide ? 64 : 32, ssh = wide ? 0 : 1;
      const uint32_t la_rev = (16 * mi + 2 * T + bb) * pitch + ((ch16 ^ ((T & 3) >> ssh)) << 4);
      const uint32_t jj = mi ? 1 : 0, isv = mi >> 1;
      const uint32_t la_halo = T ? isv * 8192 + (16 * (6 + jj) + 2 * (T - 1) + bb) * pitch + ((ch16 ^ (((T - 1) & 3) >> ssh)) << 4)
                                 : 24576 + isv * 256 + (2 * jj + bb) * pitch + ((ch16 ^ (wide ? 2 * isv + jj : 0)) << 4);
      const bool own = (lc >= 5 ? 1 : 0) == rank;
      const uint32_t dc = lc >= 5 ? lc - 5 : lc, dx1 = 5 * ECH - dc * (ECH - 64);
      uint32_t de = sb + (w4 >> 1) * REC + dc * ECH + 16 * (lane & 3) + (own ? OFF_U + 2 * rank * REC : OFF_OUT);
      const uint32_t peer = mapa(sb, rank ^ 1);
      const CUtensorMap* mp = tm.c[wide ? 1 : 0] + (w4 - 1);
      const int c0 = (wide ? (G0 & ~3) : G0) * 8, t0 = 48 + 8 * rank;
      mbar_wait(sb + B_KF0 + 8, 0);
      const uint2 wsh = lds64(sb + OFF_SH + hh * 64 + (lane >> 2) * 8);
      const __nv_bfloat162 wa = *reinterpret_cast<const __nv_bfloat162*>(&wsh.x), wb = *reinterpret_cast<const __nv_bfloat162*>(&wsh.y);
      cl_wait();
      uint32_t sl = 1, ph = 0;
#pragma unroll 1
      for (int n = 0; n < 8; n++) {
        const uint32_t pl = sb + slot_off(sl);
        if (n >= (w4 ? 4 : 2)) mbar_wait(sb + B_ERDY + 16 * (n - 2) + 8 * (rank ^ 1), 0);
        mbar_wait(sb + B_TFULL + 8 * sl, ph);
        if (w4 == 3) STAMP(64 + n);
        if (n == 7 && w4) ld_stats(na, nc, g_stat1 + 128 * (12 + w4) + 2 * lane);
        uint32_t pm2, pp, vm1, dummy, kk[8], vv[8];
        uint4 xa, xb;
        ldsm4t(pl + 16384 + (la_rev ^ pitch), xa.x, xa.y, xa.z, xa.w);
        ldsm4t(pl + 16384 + (la_rev ^ pitch) + 64 * pitch, xb.x, xb.y, xb.z, xb.w);
        ldsm4t(pl + la_halo, pm2, pp, vm1, dummy);
        ldsm4t(pl + la_rev, kk[0], kk[1], kk[2], kk[3]);
        ldsm4t(pl + 8192 + la_rev, vv[0], vv[1], vv[2], vv[3]);
        ldsm4t(pl + la_rev + 64 * pitch, kk[4], kk[5], kk[6], kk[7]);
        ldsm4t(pl + 8192 + la_rev + 64 * pitch, vv[4], vv[5], vv[6], vv[7]);
        if (valid) { sts128(de + 256, xa); sts128(de + dx1, xb); }
        uint32_t qp = prmt(pp, pm2, 0x5432);
        uint32_t up = shiftmul(wa, wb, pp, qp, pm2, prmt(pm2, pm2, 0x3232), vm1);
#pragma unroll
        for (int j = 0; j < 8; j++) {
          const uint32_t qc = prmt(kk[j], pp, 0x5432);
          const uint32_t uc = shiftmul(wa, wb, kk[j], qc, pp, qp, vv[j]);
          pp = kk[j]; qp = qc;
          kk[j] = prmt(uc, up, 0x5432); vv[j] = uc; up = uc;
          if ((j & 1) && valid) sts128((j >= 4 ? de ^ 32 : de) + (j >> 1) * 64, make_uint4(kk[j - 1], vv[j - 1], kk[j], vv[j]));
        }
        de += own ? 4 * REC : (n == 3 ? 0u - 6 * REC : 2 * REC);
        bar_sync(2, 128);
        if (w4 == 0) {
          if (elect1()) {
            mbar_arrive(sb + B_ERDY + 16 * n + 8 * rank);
            fence_async_s();
            asm volatile("cp.async.bulk.shared::cluster.shared::cta.mbarrier::complete_tx::bytes [%0], [%1], %2, [%3];"
                         ::"r"(peer + OFF_U + (4 * n + 2 * rank) * REC), "r"(sb + OFF_OUT + (n & 3) * 2 * REC), "r"(2 * REC),
                           "r"(peer + B_ERDY + 16 * n + 8 * rank) : "memory");
          }
          __syncwarp();
        } else if (n < 5) {
          if (elect1()) {
            const uint32_t b = sb + B_TFULL + 8 * sl;
            tma4d(pl + (w4 - 1) * 8192, mp, c0, 16 * n + t0, 0, b);
            if (w4 < 3) tma4d(pl + 24320 + w4 * 256, mp + 3, c0, 16 * n + t0 - 1, 6, b);
            else mbar_expect(b, wide ? 25088 : 12544);
          }
          __syncwarp();
        }
        if (++sl == 3) { sl = 0; ph ^= 1; }
      }
      if (w4 == 0) ld_stats(na, nc, g_stat1 + 128 * 12 + 2 * lane);
      if (w4 && elect1()) {
        tma3d(sb + OFF_W + (w4 - 1) * 16384, &tm.w1, 192 * TILE_F(lid), w4 - 1, sb + B_WFULL + 8 * (w4 - 1));
        tma3d(sb + OFF_W + (w4 - 1) * 16384 + 8192, &tm.w3, 192 * TILE_F(lid), w4 - 1, sb + B_WFULL + 8 * (w4 - 1));
        mbar_expect(sb + B_WFULL + 8 * (w4 - 1), 16384);
      }
      __syncwarp();
    }
    } else {
    ROLE_IDS
    {
      const int lid = logical_id();
      const int row0 = 128 * (w4 + (lane >> 4) * 4) + lid;
      const uint4* xr = reinterpret_cast<const uint4*>(pr.x + row0 * 640) + (lane & 15);
      const unsigned dn = ld_relaxed(&g_done);
      uint4 xv[5];
#pragma unroll
      for (int q = 0; q < 5; q++) xv[q] = ldg128(xr + q * 16);
      if (w4 == 3 && elect1()) { prefetch_tm(&tm.w1); prefetch_tm(&tm.w3); prefetch_tm(&tm.h); prefetch_tm(&tm.hr); prefetch_tm(&tm.w2); }
      __syncwarp();
      cl_wait();
      const unsigned tag = (dn / NCTA + 1) & 3;
      if (tid == 384) { sts32(sb + OFF_EP, dn / NCTA + 1); mbar_arrive(sb + B_EP); }
#pragma unroll 1
      for (int h = 0; h < 2; h++) {
        const float pv = bflo(__shfl_sync(0xffffffff, xv[0].x, lane & 16));
        float s0 = 0.f, q0 = 0.f, s1 = 0.f, q1 = 0.f;
#pragma unroll
        for (int q = 0; q < 5; q++) {
          float a = bflo(xv[q].x) - pv, b = bfhi(xv[q].x) - pv;
          s0 += a + b; q0 = fmaf(a, a, fmaf(b, b, q0));
          a = bflo(xv[q].y) - pv; b = bfhi(xv[q].y) - pv;
          s1 += a + b; q1 = fmaf(a, a, fmaf(b, b, q1));
          a = bflo(xv[q].z) - pv; b = bfhi(xv[q].z) - pv;
          s0 += a + b; q0 = fmaf(a, a, fmaf(b, b, q0));
          a = bflo(xv[q].w) - pv; b = bfhi(xv[q].w) - pv;
          s1 += a + b; q1 = fmaf(a, a, fmaf(b, b, q1));
        }
        s0 += s1; q0 += q1;
        asm volatile("" : "+f"(s0), "+f"(q0));
        if (h == 0) {
#pragma unroll
          for (int q = 0; q < 5; q++) xv[q] = ldg128(xr + 1024 * 80 + q * 16);
        }
        const bool o1 = lane & 1;
        float v = (o1 ? q0 : s0) + __shfl_xor_sync(0xffffffff, o1 ? s0 : q0, 1);
#pragma unroll
        for (int o = 8; o > 1; o >>= 1) v += __shfl_xor_sync(0xffffffff, v, o);
        const float dm = v * (1.f / 640.f), e2 = __shfl_xor_sync(0xffffffff, dm, 1);
        const float r = rsqrtf(fmaxf(e2 - dm * dm, 0.f) + LN_EPS);
        if ((lane & 15) == 0) st_relaxed64(&g_stat1[1024 * h + row0], (__float_as_uint(r) & ~3u) | tag, __float_as_uint((pv + dm) * r));
        if (h == 0 && w4 == 1 && elect1()) {
#pragma unroll
          for (int c = 0; c < 2; c++) bulk_g2s(sb + OFF_KFL + c * KS, pr.kf + (5 * lid + 3 + c) * 2048, 4096, sb + B_KFL0);
          mbar_expect(sb + B_KFL0, 2 * 4096);
        }
        __syncwarp();
        if (w4 == 0) STAMP(118 + h);
      }
      ld_stats(na, nc, g_stat1 + 128 * w4 + 2 * lane);
    }
    }
    {
      ROLE_IDS
      const int q0 = wg == 2 ? 3 : 0;
      const uint32_t db = (uint32_t)mkdesc(sb + OFF_ID, 0, 128, 0), da = (uint32_t)mkdesc(sb + OFF_P + 128, PR - 32, 128, 0), xs = (lane & 4) ? 64 : ECH;
      const uint32_t xa = sb + OFF_U + 2 * REC * w4 + ((lane & 4) ? 5 * ECH : 256) + 16 * (lane >> 3) + 4 * (lane & 3);
      uint32_t* hp = reinterpret_cast<uint32_t*>(g_hT) + logical_id() * 1024 + 64 * w4 + lane;
      const float2* sp = g_stat1 + 128 * w4 + 2 * lane;
      mbar_wait(sb + B_EP, 0);
      const uint32_t tag = lds32(sb + OFF_EP);
#pragma unroll 1
      for (int q = q0; q < (wg == 2 ? 4 : 3); q++) {
        if (q == 1 && w4 == 1) { mbar_wait(sb + B_KF0, 0); patch_tap0(sb, OFF_KFL, 3, 2, B_KFL0, B_KFL, lane); }
        check_stats(na, nc, sp + 512 * q, tag);
        const float4 sa = na, sc = nc;
        if (q < 3) ld_stats(na, nc, sp + 512 * (q + 1));
        float y[3][4];
        uint32_t xl[3], xh[3];
        mbar_wait(sb + B_YRDY + 8 * q, 0);
        wg_fence();
#pragma unroll
        for (int i = 0; i < 3; i++) red_sum(y[i], da + q * 64 + i * (4 * PR / 16), db);
        wg_commit();
#pragma unroll
        for (int i = 0; i < 3; i++) { xl[i] = lds32(xa + q * 8 * REC + i * xs); xh[i] = lds32(xa + q * 8 * REC + i * xs + REC); }
        wg_wait<0>();
#pragma unroll
        for (int i = 0; i < 3; i++) red_fin(hp + q * 256 + i * 131072, y[i], xl[i], xh[i], sa, sc);
        __syncwarp();
        if (lane == 0 && q >= 2) mbar_arrive(sb + B_EDONE);
        if (w4 == 0) STAMP(32 + q);
      }
      if (warp == 10) {
        unsigned* cnt = &g_hcnt[(cta & 3) * 32];
        mbar_wait(sb + B_EDONE, 0);
        if (lane == 0) { fence_rel(); red_add(cnt, 1); }
        __syncwarp();
        bar_arrive(6, 64);
        STAMP(47);
      }
      if (wg == 3) {
        if (W2AFT) mbar_wait(sb + B_ERDY + 112 + 8 * (cta & 1), 0);
        if (elect1()) {
          const int lid = logical_id(), m = TILE_M(lid), f = TILE_F(lid);
#pragma unroll 1
          for (int u = 3 * w4; u < 3 * w4 + 3; u++) {
            const int kg = 6 * m + (u >> 1), nb = kg >> 3;
            asm volatile("cp.async.bulk.tensor.3d.shared::cluster.global.mbarrier::complete_tx::bytes [%0], [%1, {%3, %4, %5}], [%2];"
                         ::"r"(sb + u * 1280), "l"(&tm.w2), "r"(sb + B_W2G), "r"(0), "r"(64 * (3 * (2 * (nb & 3) + (f & 1)) + (nb >> 2)) + 8 * (kg & 7)),
                           "r"(10 * ((u & 1) ? f : f ^ 1)) : "memory");
          }
          mbar_expect(sb + B_W2G, 3840);
        }
        __syncwarp();
        check_stats(na, nc, sp + 512 * 3, tag);
#pragma unroll 1
        for (int q = 0; q < 4; q += 2) {
          float4 sa[2], sc[2];
          ld_stats(sa[0], sc[0], sp + 512 * q); ld_stats(sa[1], sc[1], sp + 512 * q + 512);
          float y[4][4];
          uint32_t xl[4], xh[4];
#pragma unroll
          for (int i = 0; i < 4; i++) { const uint32_t a = xa + (q + (i >> 1)) * 8 * REC + (3 + (i & 1)) * xs; xl[i] = lds32(a); xh[i] = lds32(a + REC); }
          if (q) mbar_wait(sb + B_EDONE, 0);
          mbar_wait(sb + B_YRDY + 8 * q + 8, 1);
          wg_fence();
#pragma unroll
          for (int i = 0; i < 4; i++) red_sum(y[i], da + (q + (i >> 1)) * 64 + (1 + (i & 1)) * (4 * PR / 16), db);
          wg_commit();
          wg_wait<0>();
#pragma unroll
          for (int i = 0; i < 4; i++) red_fin(hp + (q + (i >> 1)) * 256 + (3 + (i & 1)) * 131072, y[i], xl[i], xh[i], sa[i >> 1], sc[i >> 1]);
          if (w4 == 0) STAMP(36 + q);
        }
        __syncwarp();
        if (lane == 0) mbar_arrive(sb + B_CDONE);
      }
    }
    if (CR < 216) asm volatile("setmaxnreg.dec.sync.aligned.u32 40;");
    ROLE_IDS
    mbar_wait(sb + B_EP, 0);
    const unsigned epoch = lds32(sb + OFF_EP);
    if (wg == 2) {
    const int lid = logical_id(), m = TILE_M(lid), f = TILE_F(lid);
    if (w4 == 0) {
      if (elect1()) {
        int c0 = 192 * f, r0 = 4;
        unsigned w2c = 0;
#pragma unroll 1
        for (int s = 4; s < 30; s++) {
          const uint32_t sl = s & 3;
          wait_w13(sb + B_WEMPTY + 8 * sl, ((s >> 2) & 1) ^ 1, sb + OFF_W + sl * 16384, sb + OFF_W + sl * 16384 + 8192, &tm.w1, &tm.w3,
                   c0, (r0 & 1) * 64, r0 >> 1, sb + B_WFULL + 8 * sl);
          if (++r0 == 10) { r0 = 0; c0 += 64; }
          if (s == 28) w2c = ld_relaxed(&g_w2cnt[f * 32]);
        }
        unsigned c = 0;
        while ((int)(w2c - 16 * epoch) < 0) { w2c = ld_relaxed(&g_w2cnt[f * 32]); SPIN_GUARD(c); }
        fence_async_g();
        uint32_t r = 0, ph = 0;
#pragma unroll 1
        for (int s = 0; s < 16; s++) {
          const uint32_t buf = r < 4 ? 2 + ((r + 2) & 3) : r - 4;
          const uint32_t bf = sb + (r < 4 ? B_WFULL - 16 : B_AFULL + 64) + 8 * buf, be = sb + (r < 4 ? B_WEMPTY - 16 : B_AEMPTY + 64) + 8 * buf;
          wait_bulk(be, ph ^ ((r & 6) == 2 ? 1 : 0), sb + OFF_W - 32768 + buf * 16384, g_w2t + f * 245760 + s * 15360, 15360, bf);
          if (++r == 6) { r = 0; ph ^= 1; }
        }
      }
    } else if (w4 == 1) {
      mbar_wait(sb + B_W2G, 0);
      bar_sync(6, 64);
      if (elect1()) {
#pragma unroll 1
        for (int u = 0; u < 12; u++) {
          const int kg = 6 * m + (u >> 1);
          asm volatile("cp.async.bulk.global.shared::cta.bulk_group [%0], [%1], 1280;"
                       ::"l"(g_w2t + f * 245760 + (kg < 64 ? kg * 2560 + (u & 1) * 1280 : 163840 + (u & 1) * 40960 + (kg - 64) * 1280)), "r"(sb + u * 1280) : "memory");
        }
        asm volatile("cp.async.bulk.commit_group;\ncp.async.bulk.wait_group 0;\nfence.proxy.async.global;" ::: "memory");
      }
      __syncwarp();
      bar_arrive(3, 320);
      STAMP(28);
#pragma unroll 1
      for (int st = 0; st < 3; st++) {
        if (st < 2) { mbar_wait(sb + (st ? B_CDONE : B_EDONE), 0); fence_async_s(); }
        if (st != 1) {
          unsigned c = 0;
          const unsigned* cp = &g_hcnt[(2 * st + (lane & 3)) * 32];
          while (!__all_sync(0xffffffff, (int)(ld_relaxed(cp) - 32 * epoch) >= 0)) SPIN_GUARD(c);
          fence_async_g();
        }
        STAMP(50 + st);
        if (elect1()) {
#pragma unroll 1
          for (int kb = 3 * st; kb < (st == 2 ? 10 : 3 * st + 3); kb++) {
            tma2d(sb + OFF_A + kb * 16384, &tm.h, 128 * m, 64 * kb, sb + B_AFULL + 8 * kb);
            tma2d(sb + OFF_A + kb * 16384 + 8192, &tm.h, 128 * m + 64, 64 * kb, sb + B_AFULL + 8 * kb);
            mbar_expect(sb + B_AFULL + 8 * kb, 16384);
          }
        }
        __syncwarp();
      }
      STAMP(24);
      mbar_wait(sb + B_AEMPTY, 0);
#pragma unroll 1
      for (int p = 0; p < 3; p++) {
        unsigned c = 0;
        while (!__all_sync(0xffffffff, ld_relaxed(&g_gflag[m * 32 + p * 8 + 2 * (lane & 3) + (f & 1)]) == epoch)) SPIN_GUARD(c);
        STAMP(25 + p);
        fence_async_g();
        if (elect1()) {
#pragma unroll 1
          for (int j = 0; j < 4; j++) {
            const uint32_t s = (4 * p + j) & 7;
            wait_bulk(sb + B_AEMPTY + 8 * s, p >> 1, sb + OFF_A + s * 16384, g_g + (m * 24 + 3 * (2 * j + (f & 1)) + p) * 16384, 16384, sb + B_AFULL + 8 * s);
          }
        }
        __syncwarp();
      }
      mbar_wait(sb + B_AEMPTY + 56, 1);
      if (elect1()) {
#pragma unroll
        for (int i = 0; i < 2; i++)
          asm volatile("cp.async.bulk.tensor.3d.shared::cluster.global.mbarrier::complete_tx::bytes [%0], [%1, {%3, %4, %5}], [%2];"
                       ::"r"(sb + OFF_A + 4 * 16384 + 20480 + i * 10240), "l"(&tm.hr), "r"(sb + B_AFULL + 56), "r"(128 * m + 64 * i), "r"(0), "r"(16 * f) : "memory");
        mbar_expect(sb + B_AFULL + 56, 20480);
      }
    } else {
      if (w4 == 3) {
        mbar_wait(sb + B_EDONE, 0);
        if (elect1()) {
          tma3d(sb + OFF_W + 49152, &tm.w1, 192 * f, 3, sb + B_WFULL + 24);
          tma3d(sb + OFF_W + 49152 + 8192, &tm.w3, 192 * f, 3, sb + B_WFULL + 24);
          mbar_expect(sb + B_WFULL + 24, 16384);
        }
        __syncwarp();
        mbar_wait(sb + B_AFULL, 1);
#pragma unroll 1
        for (int p = 0; p < 3; p++) fetch_colsum(sb, f, p, lane, epoch);
      } else {
        mbar_wait(sb + B_CDONE, 0);
        if (lane == 0) { fence_rel(); red_add(&g_hcnt[(4 + (lid & 3)) * 32], 1); }
        __syncwarp();
        STAMP(48);
#pragma unroll 1
        for (int p = 0; p < 3; p++) {
          bar_sync(3 + p, p ? 288 : 320);
          if (lane == 0) { fence_rel(); st_relaxed(&g_gflag[m * 32 + p * 8 + f], epoch); if (p == 0) red_add(&g_w2cnt[f * 32], 1); }
          __syncwarp();
          STAMP(20 + p);
        }
      }
    }
    } else {
    const int lid = logical_id(), m = TILE_M(lid), f = TILE_F(lid);
    const unsigned tag = epoch & 3;
    {
      const uint32_t a0 = sb + OFF_A + (f >> 2) * 8192 + (16 * w4 + (lane & 15)) * 128 + (((2 * (f & 3) + (lane >> 4)) ^ (lane & 7)) << 4);
      float s0 = 0.f, q0 = 0.f, s1 = 0.f, q1 = 0.f;
#pragma unroll 1
      for (int kb = 0; kb < 10; kb += 2) {
        uint32_t v[8];
        mbar_wait(sb + B_AFULL + 8 * kb, 1);
        ldsm4t(a0 + kb * 16384, v[0], v[1], v[2], v[3]);
        mbar_wait(sb + B_AFULL + 8 * kb + 8, 1);
        ldsm4t(a0 + kb * 16384 + 16384, v[4], v[5], v[6], v[7]);
#pragma unroll
        for (int i = 0; i < 8; i++) {
          const float a = bflo(v[i]), b = bfhi(v[i]);
          if (i & 2) { s1 += a + b; q1 = fmaf(a, a, fmaf(b, b, q1)); } else { s0 += a + b; q0 = fmaf(a, a, fmaf(b, b, q0)); }
        }
      }
      const bool o1 = lane & 1;
      float s = (o1 ? s1 : s0) + __shfl_xor_sync(0xffffffff, o1 ? s0 : s1, 1), q = (o1 ? q1 : q0) + __shfl_xor_sync(0xffffffff, o1 ? q0 : q1, 1);
      s += __shfl_xor_sync(0xffffffff, s, 2); q += __shfl_xor_sync(0xffffffff, q, 2);
      if (!(lane & 2)) st_relaxed64(&g_stat2[(128 * m + 16 * f + 8 * (lane & 1) + (lane >> 2)) * 4 + w4], (__float_as_uint(s) & ~3u) | tag, __float_as_uint(q));
      const float2* p = g_stat2 + (128 * m + (tid & 127)) * 4;
      float4 u, v;
      unsigned c = 0;
      for (;;) {
        asm volatile("ld.relaxed.gpu.global.v4.f32 {%0,%1,%2,%3}, [%4];" : "=f"(u.x), "=f"(u.y), "=f"(u.z), "=f"(u.w) : "l"(p) : "memory");
        asm volatile("ld.relaxed.gpu.global.v4.f32 {%0,%1,%2,%3}, [%4];" : "=f"(v.x), "=f"(v.y), "=f"(v.z), "=f"(v.w) : "l"(p + 2) : "memory");
        const uint32_t bad = (__float_as_uint(u.x) ^ tag) | (__float_as_uint(u.z) ^ tag) | (__float_as_uint(v.x) ^ tag) | (__float_as_uint(v.z) ^ tag);
        if (__all_sync(0xffffffff, (bad & 3) == 0)) break;
        SPIN_GUARD(c);
      }
      const float mean = ((u.x + u.z) + (v.x + v.z)) * (1.f / 640.f);
      sts64f(sb + OFF_ST2 + (tid & 127) * 8, rsqrtf(fmaxf(((u.y + u.w) + (v.y + v.w)) * (1.f / 640.f) - mean * mean, 0.f) + LN_EPS), mean);
      __syncwarp();
      if (lane == 0) mbar_arrive(sb + B_S2);
      if (w4 == 0) STAMP(49);
    }
    }
  }
}

typedef CUresult (*EncFn)(CUtensorMap*, CUtensorMapDataType, cuuint32_t, void*, const cuuint64_t*, const cuuint64_t*,
                          const cuuint32_t*, const cuuint32_t*, CUtensorMapInterleave, CUtensorMapSwizzle,
                          CUtensorMapL2promotion, CUtensorMapFloatOOBfill);

void make_map2(EncFn enc, CUtensorMap* tm, void* p, uint64_t inner, uint64_t outer) {
  cuuint64_t gd[2] = {inner, outer}, gs[1] = {inner * 2};
  cuuint32_t bd[2] = {64, 64}, es[2] = {1, 1};
  enc(tm, CU_TENSOR_MAP_DATA_TYPE_BFLOAT16, 2, p, gd, gs, bd, es, CU_TENSOR_MAP_INTERLEAVE_NONE, CU_TENSOR_MAP_SWIZZLE_128B,
      CU_TENSOR_MAP_L2_PROMOTION_L2_128B, CU_TENSOR_MAP_FLOAT_OOB_FILL_NONE);
}
void make_map3(EncFn enc, CUtensorMap* tm, void* p) {
  cuuint64_t gd[3] = {1536, 128, 5}, gs[2] = {5 * 3072, 3072};
  cuuint32_t bd[3] = {64, 64, 1}, es[3] = {1, 1, 1};
  enc(tm, CU_TENSOR_MAP_DATA_TYPE_BFLOAT16, 3, p, gd, gs, bd, es, CU_TENSOR_MAP_INTERLEAVE_NONE, CU_TENSOR_MAP_SWIZZLE_128B,
      CU_TENSOR_MAP_L2_PROMOTION_L2_128B, CU_TENSOR_MAP_FLOAT_OOB_FILL_NONE);
}
void make_map4(EncFn enc, CUtensorMap* tm, void* p, bool wide, bool halo, bool perm = false) {
  cuuint64_t gd[4] = {640, 2, 128, 8}, gs[3] = {perm ? 8 * 1280u : 1280u, 16 * 1280, perm ? 1280u : 2 * 1280u};
  cuuint32_t bd[4] = {wide ? 32u : 16u, 2, halo ? 1u : 8u, halo ? 2u : 8u}, es[4] = {1, 1, 1, 1};
  enc(tm, CU_TENSOR_MAP_DATA_TYPE_BFLOAT16, 4, p, gd, gs, bd, es, CU_TENSOR_MAP_INTERLEAVE_NONE,
      wide ? CU_TENSOR_MAP_SWIZZLE_64B : CU_TENSOR_MAP_SWIZZLE_32B, CU_TENSOR_MAP_L2_PROMOTION_L2_128B, CU_TENSOR_MAP_FLOAT_OOB_FILL_NONE);
}

}

extern "C" void kernel_launch(void* const* d_in, const int* in_sizes, int n_in, void* d_out, int out_size) {
  (void)in_sizes; (void)n_in; (void)out_size;
  void* fn = nullptr;
  cudaDriverEntryPointQueryResult qr;
  cudaGetDriverEntryPoint("cuTensorMapEncodeTiled", &fn, cudaEnableDefault, &qr);
  EncFn enc = (EncFn)fn;
  void* hT = nullptr;
  cudaGetSymbolAddress(&hT, g_hT);
  Maps tm;
  make_map2(enc, &tm.h, hT, 2048, 640);
  {
    cuuint64_t gd[3] = {2048, 5, 128}, gs[2] = {128 * 4096, 4096};
    cuuint32_t bd[3] = {64, 5, 16}, es[3] = {1, 1, 1};
    enc(&tm.hr, CU_TENSOR_MAP_DATA_TYPE_BFLOAT16, 3, hT, gd, gs, bd, es, CU_TENSOR_MAP_INTERLEAVE_NONE, CU_TENSOR_MAP_SWIZZLE_128B,
        CU_TENSOR_MAP_L2_PROMOTION_L2_128B, CU_TENSOR_MAP_FLOAT_OOB_FILL_NONE);
  }
  {
    cuuint64_t gd[3] = {8, 1536, 80}, gs[2] = {1280, 16};
    cuuint32_t bd[3] = {8, 8, 10}, es[3] = {1, 1, 1};
    enc(&tm.w2, CU_TENSOR_MAP_DATA_TYPE_BFLOAT16, 3, d_in[9], gd, gs, bd, es, CU_TENSOR_MAP_INTERLEAVE_NONE, CU_TENSOR_MAP_SWIZZLE_NONE,
        CU_TENSOR_MAP_L2_PROMOTION_L2_128B, CU_TENSOR_MAP_FLOAT_OOB_FILL_NONE);
  }
  make_map3(enc, &tm.w1, d_in[7]);
  make_map3(enc, &tm.w3, d_in[8]);
  for (int w = 0; w < 2; w++) {
    make_map4(enc, &tm.c[w][0], d_in[1], w, false);
    make_map4(enc, &tm.c[w][1], d_in[2], w, false);
    make_map4(enc, &tm.c[w][2], d_in[0], w, false);
    make_map4(enc, &tm.c[w][3], d_in[1], w, true);
    make_map4(enc, &tm.c[w][4], d_in[2], w, true);
  }
  Params p;
  p.x = (const __nv_bfloat16*)d_in[0]; p.k = (const __nv_bfloat16*)d_in[1]; p.v = (const __nv_bfloat16*)d_in[2];
  p.shift = (const __nv_bfloat16*)d_in[3]; p.kf = (const __nv_bfloat16*)d_in[4]; p.D = (const __nv_bfloat16*)d_in[5];
  p.w2 = (const __nv_bfloat16*)d_in[9];
  p.out = (__nv_bfloat16*)d_out; p.z = 0;
  cudaFuncSetAttribute(h3_ffn_kernel, cudaFuncAttributeMaxDynamicSharedMemorySize, SMEM_BYTES);
  h3_ffn_kernel<<<NCTA, 512, SMEM_BYTES>>>(p, tm);
}
```

```cpp
#include <cuda_runtime.h>
#include <cuda_bf16.h>
#include <cuda.h>
#include <stdint.h>

namespace {

constexpr int NCTA = 132;
constexpr float LN_EPS = 1e-5f;
#define AUX_DELAY 9500
#define W2PF_DELAY 9000
#define PF2 1
#define KVPF 0
#define KVPF_T0 500
#define KFPOS 1
#define MAP2 0
#define TILE_M(l) ((l) >> 3)
#define TILE_F(l) ((l) & 7)
#define P2K0 1
#define USE_TANH 1
#define NSCALE 0.5f
#define RSCALE 2.0f
#define HEADV 1
#define G2STAMP 0
#define P2D0 20
#define P2D1 20
#define KFPOSH 0
#define CR 168
#define P1K0 2
#define RELFIRST 1
#define MSTART 0
#define LATEN 34
#define NPOLL 0
#define W2N 42
#define W2KB 5
#define W2GN 6
#define W2AFT 1
#define A1AFT 0
#define XE 5
#define E0S (XE > 2 ? 10 + XE : 12)
#define PUB0 416
#define INCS 19
#define LN2SLEEP 0
#define N80 0
#define W2SLEEP 0
#define W2GAP 100
#define WAVE_T0 3000
#define WAVE_DT 1000

__device__ __align__(1024) __nv_bfloat16 g_hT[640 * 2048];
__device__ __align__(1024) unsigned char g_g[16 * 24 * 16384];
__device__ __align__(1024) unsigned char g_w2t[8 * 245760];
__device__ __align__(128) float2 g_stat1[2048];
__device__ __align__(128) float2 g_stat2[2048 * 4];
__device__ __align__(128) float g_colsum[8 * 3 * 128];
__device__ __align__(128) unsigned g_hcnt[10 * 32];
__device__ __align__(128) unsigned g_gflag[16 * 32];
__device__ __align__(128) unsigned g_w2cnt[8 * 32];
__device__ __align__(128) unsigned g_done;
#define STAMP(i) do {} while (0)
#define STAMP0(i) do {} while (0)
#define GSTAMP(i) do {} while (0)
#define STAMPM(i, m) do {} while (0)

constexpr uint32_t OFF_A = 0;
constexpr uint32_t OFF_W = 163840;
constexpr uint32_t OFF_MISC = 229376;
constexpr uint32_t OFF_ST2 = OFF_MISC;
constexpr uint32_t OFF_CS = OFF_MISC + 1024;
constexpr uint32_t OFF_BAR = OFF_MISC + 2560;
constexpr uint32_t SMEM_BYTES = 232448;
constexpr uint32_t B_WFULL = OFF_BAR, B_WEMPTY = OFF_BAR + 32, B_AFULL = OFF_BAR + 64, B_AEMPTY = OFF_BAR + 144;
constexpr uint32_t B_S2 = OFF_BAR + 224, B_CS = OFF_BAR + 232  ;
constexpr uint32_t B_ERDY = OFF_BAR + 256  , B_W2G = OFF_BAR + 384, B_EDONE = OFF_BAR + 392, B_YRDY = OFF_BAR + 400  , B_KFL0 = OFF_BAR + 432, B_KFL = OFF_BAR + 440, B_KF = OFF_BAR + 448, B_CDONE = OFF_BAR + 456;
constexpr uint32_t B_KF0 = OFF_BAR + 464  , B_EP = OFF_BAR + 480, OFF_EP = OFF_BAR + 488, B_XFREE = OFF_BAR + 496, B_XIN = OFF_BAR + 504;
constexpr uint32_t B_TFULL = B_AFULL;
constexpr uint32_t TILE = 25600;
constexpr uint32_t REC = 1920, ECH = 320;
constexpr uint32_t OFF_OUT = TILE;
constexpr uint32_t PR = 4224, OFF_P = OFF_OUT + 8 * REC;
constexpr uint32_t KS = 4224, OFF_KFL = OFF_P + 12 * PR + 128;
constexpr uint32_t OFF_U = OFF_KFL - 128 + 2 * KS + REC;
constexpr uint32_t OFF_ID = OFF_U + 32 * REC, OFF_SH = OFF_ID + 128, OFF_D = OFF_SH + 128;
constexpr uint32_t OFF_KFE = OFF_W + 2 * TILE + 384;
static_assert(OFF_D + 32 <= OFF_W && (OFF_U & 63) == 0 && OFF_KFE + 3 * KS - 128 <= OFF_MISC && OFF_P + 4 * PR >= 49152, "layout");
__host__ __device__ constexpr uint32_t slot_off(uint32_t sl) { return sl ? OFF_W - TILE + sl * TILE : 0; }

__device__ __forceinline__ void mbar_init(uint32_t b, uint32_t c) { asm volatile("mbarrier.init.shared::cta.b64 [%0], %1;" ::"r"(b), "r"(c) : "memory"); }
__device__ __forceinline__ void mbar_expect(uint32_t b, uint32_t n) { asm volatile("mbarrier.arrive.expect_tx.shared::cta.b64 _, [%0], %1;" ::"r"(b), "r"(n) : "memory"); }
__device__ __forceinline__ void mbar_arrive(uint32_t b) { asm volatile("mbarrier.arrive.shared::cta.b64 _, [%0];" ::"r"(b) : "memory"); }
__device__ __forceinline__ void mbar_wait(uint32_t b, uint32_t par) {
  asm volatile(
      "{.reg .pred p; .reg .u32 c; mov.u32 c, 0;\n"
      "LW%=: mbarrier.try_wait.parity.shared::cta.b64 p, [%0], %1;\n"
      "@p bra LD%=;\n"
      "add.u32 c, c, 1; setp.lt.u32 p, c, 4000000; @p bra LW%=;\n"
      "trap;\n"
      "LD%=: }\n" ::"r"(b), "r"(par) : "memory");
}
__device__ __forceinline__ void mbar_wait_u(uint32_t b, uint32_t par) {
  asm volatile("{.reg .pred p;\nLW%=: mbarrier.try_wait.parity.shared::cta.b64 p, [%0], %1;\n@!p bra LW%=;}\n" ::"r"(b), "r"(par) : "memory");
}
__device__ __forceinline__ bool elect1() { uint32_t p; asm volatile("{.reg .pred P; elect.sync _|P, 0xffffffff; selp.u32 %0,1,0,P;}" : "=r"(p)); return p; }
__device__ __forceinline__ void bar_sync(int id, int n) { asm volatile("bar.sync %0, %1;" ::"r"(id), "r"(n) : "memory"); }
__device__ __forceinline__ void bar_arrive(int id, int n) { asm volatile("bar.arrive %0, %1;" ::"r"(id), "r"(n) : "memory"); }
__device__ __forceinline__ void fence_async_s() { asm volatile("fence.proxy.async.shared::cta;" ::: "memory"); }
__device__ __forceinline__ void fence_async_g() { asm volatile("fence.acquire.gpu;\nfence.proxy.async.global;" ::: "memory"); }
__device__ __forceinline__ void fence_rel() { asm volatile("fence.release.gpu;" ::: "memory"); }
__device__ __forceinline__ int tid_x() { int v; asm volatile("mov.u32 %0, %%tid.x;" : "=r"(v)); return v; }
__device__ __forceinline__ void cl_arrive_rlx() { asm volatile("barrier.cluster.arrive.relaxed.aligned;" ::: "memory"); }
__device__ __forceinline__ void cl_wait() { asm volatile("barrier.cluster.wait.acquire.aligned;" ::: "memory"); }
__device__ __forceinline__ uint32_t mapa(uint32_t a, uint32_t r) { uint32_t o; asm volatile("mapa.shared::cluster.u32 %0, %1, %2;" : "=r"(o) : "r"(a), "r"(r)); return o; }
__device__ __forceinline__ void mbar_arrive_n(uint32_t b, uint32_t n) { asm volatile("mbarrier.arrive.shared::cta.b64 _, [%0], %1;" ::"r"(b), "r"(n) : "memory"); }
__device__ __forceinline__ bool mbar_test(uint32_t b, uint32_t par) {
  uint32_t ok; asm volatile("{.reg .pred p; mbarrier.test_wait.parity.shared::cta.b64 p, [%1], %2; selp.u32 %0,1,0,p;}" : "=r"(ok) : "r"(b), "r"(par) : "memory"); return __all_sync(0xffffffff, ok);
}
__device__ __forceinline__ void st_async4(uint32_t a, uint32_t x, uint32_t y, uint32_t z, uint32_t w, uint32_t bar) {
  asm volatile("st.async.weak.shared::cluster.mbarrier::complete_tx::bytes.v4.b32 [%0], {%1,%2,%3,%4}, [%5];" ::"r"(a), "r"(x), "r"(y), "r"(z), "r"(w), "r"(bar) : "memory");
}
__device__ __forceinline__ void stsm2t(uint32_t a, uint32_t r0, uint32_t r1) {
  asm volatile("stmatrix.sync.aligned.m8n8.x2.trans.shared.b16 [%0], {%1,%2};" ::"r"(a), "r"(r0), "r"(r1) : "memory");
}
__device__ __forceinline__ uint4 ldg128(const void* p) { uint4 v; asm volatile("ld.global.nc.v4.u32 {%0,%1,%2,%3}, [%4];" : "=r"(v.x), "=r"(v.y), "=r"(v.z), "=r"(v.w) : "l"(p)); return v; }
__device__ __forceinline__ void stg128(void* p, uint4 v) { asm volatile("st.global.v4.b32 [%0], {%1,%2,%3,%4};" ::"l"(p), "r"(v.x), "r"(v.y), "r"(v.z), "r"(v.w) : "memory"); }
__device__ __forceinline__ void prefetch_tm(const CUtensorMap* t) { asm volatile("prefetch.tensormap [%0];" ::"l"(t) : "memory"); }
__device__ __forceinline__ uint32_t lds32(uint32_t a) { uint32_t v; asm volatile("ld.shared.b32 %0, [%1];" : "=r"(v) : "r"(a) : "memory"); return v; }
__device__ __forceinline__ uint2 lds64(uint32_t a) { uint2 v; asm volatile("ld.shared.v2.b32 {%0,%1}, [%2];" : "=r"(v.x), "=r"(v.y) : "r"(a) : "memory"); return v; }
__device__ __forceinline__ uint4 lds128(uint32_t a) { uint4 v; asm volatile("ld.shared.v4.b32 {%0,%1,%2,%3}, [%4];" : "=r"(v.x), "=r"(v.y), "=r"(v.z), "=r"(v.w) : "r"(a) : "memory"); return v; }
__device__ __forceinline__ float4 lds128f(uint32_t a) { float4 v; asm volatile("ld.shared.v4.f32 {%0,%1,%2,%3}, [%4];" : "=f"(v.x), "=f"(v.y), "=f"(v.z), "=f"(v.w) : "r"(a) : "memory"); return v; }
__device__ __forceinline__ float2 lds64f(uint32_t a) { float2 v; asm volatile("ld.shared.v2.f32 {%0,%1}, [%2];" : "=f"(v.x), "=f"(v.y) : "r"(a) : "memory"); return v; }
__device__ __forceinline__ void sts32f(uint32_t a, float v) { asm volatile("st.shared.f32 [%0], %1;" ::"r"(a), "f"(v) : "memory"); }
__device__ __forceinline__ void sts32(uint32_t a, uint32_t v) { asm volatile("st.shared.b32 [%0], %1;" ::"r"(a), "r"(v) : "memory"); }
__device__ __forceinline__ void sts64f(uint32_t a, float x, float y) { asm volatile("st.shared.v2.f32 [%0], {%1,%2};" ::"r"(a), "f"(x), "f"(y) : "memory"); }
__device__ __forceinline__ void sts128(uint32_t a, uint4 v) { asm volatile("st.shared.v4.b32 [%0], {%1,%2,%3,%4};" ::"r"(a), "r"(v.x), "r"(v.y), "r"(v.z), "r"(v.w) : "memory"); }
__device__ __forceinline__ void ldsm4t(uint32_t a, uint32_t& r0, uint32_t& r1, uint32_t& r2, uint32_t& r3) {
  asm volatile("ldmatrix.sync.aligned.m8n8.x4.trans.shared.b16 {%0,%1,%2,%3}, [%4];" : "=r"(r0), "=r"(r1), "=r"(r2), "=r"(r3) : "r"(a) : "memory");
}
__device__ __forceinline__ void stsm4(uint32_t a, uint32_t r0, uint32_t r1, uint32_t r2, uint32_t r3) {
  asm volatile("stmatrix.sync.aligned.m8n8.x4.shared.b16 [%0], {%1,%2,%3,%4};" ::"r"(a), "r"(r0), "r"(r1), "r"(r2), "r"(r3) : "memory");
}
__device__ __forceinline__ void bulk_g2s(uint32_t d, const void* g, uint32_t n, uint32_t bar) {
  asm volatile("cp.async.bulk.shared::cluster.global.mbarrier::complete_tx::bytes [%0], [%1], %2, [%3];" ::"r"(d), "l"(g), "r"(n), "r"(bar) : "memory");
}
__device__ __forceinline__ void tma2d(uint32_t d, const CUtensorMap* t, int c0, int c1, uint32_t bar) {
  asm volatile("cp.async.bulk.tensor.2d.shared::cluster.global.mbarrier::complete_tx::bytes [%0], [%1, {%3, %4}], [%2];" ::"r"(d), "l"(t), "r"(bar), "r"(c0), "r"(c1) : "memory");
}
__device__ __forceinline__ void tma3d(uint32_t d, const CUtensorMap* t, int c0, int kb, uint32_t bar) {
  asm volatile("cp.async.bulk.tensor.3d.shared::cluster.global.mbarrier::complete_tx::bytes [%0], [%1, {%3, %4, %5}], [%2];" ::"r"(d), "l"(t), "r"(bar), "r"(c0), "r"((kb & 1) * 64), "r"(kb >> 1) : "memory");
}
#define WAITLOOP(b, par) "mov.u32 c, 0;\nLW%=: mbarrier.try_wait.parity.shared::cta.b64 p, [" b "], " par ";\n@p bra LD%=;\nadd.u32 c, c, 1; setp.lt.u32 p, c, 4000000; @p bra LW%=;\ntrap;\nLD%=:\n"
__device__ __forceinline__ void wait_w13(uint32_t be, uint32_t par, uint32_t d, uint32_t d2, const CUtensorMap* t1, const CUtensorMap* t3, int c0, int c1, int c2, uint32_t bf) {
  asm volatile("{.reg .pred p; .reg .u32 c;\n" WAITLOOP("%0", "%1")
               "cp.async.bulk.tensor.3d.shared::cluster.global.mbarrier::complete_tx::bytes [%2], [%4, {%6, %7, %8}], [%9];\n"
               "cp.async.bulk.tensor.3d.shared::cluster.global.mbarrier::complete_tx::bytes [%3], [%5, {%6, %7, %8}], [%9];\n"
               "mbarrier.arrive.expect_tx.shared::cta.b64 _, [%9], 16384;}\n"
               ::"r"(be), "r"(par), "r"(d), "r"(d2), "l"(t1), "l"(t3), "r"(c0), "r"(c1), "r"(c2), "r"(bf) : "memory");
}
__device__ __forceinline__ void wait_bulk(uint32_t be, uint32_t par, uint32_t d, const void* g, uint32_t n, uint32_t bf) {
  asm volatile("{.reg .pred p; .reg .u32 c;\n" WAITLOOP("%0", "%1")
               "cp.async.bulk.shared::cluster.global.mbarrier::complete_tx::bytes [%2], [%3], %4, [%5];\n"
               "mbarrier.arrive.expect_tx.shared::cta.b64 _, [%5], %4;}\n"
               ::"r"(be), "r"(par), "r"(d), "l"(g), "r"(n), "r"(bf) : "memory");
}
__device__ __forceinline__ void tma4d(uint32_t d, const CUtensorMap* t, int c0, int c2, int c3, uint32_t bar) {
  asm volatile("cp.async.bulk.tensor.4d.shared::cluster.global.mbarrier::complete_tx::bytes [%0], [%1, {%3, %6, %4, %5}], [%2];" ::"r"(d), "l"(t), "r"(bar), "r"(c0), "r"(c2), "r"(c3), "r"(0) : "memory");
}
__device__ __forceinline__ void prefetch_l2(const void* g, uint32_t n) { asm volatile("cp.async.bulk.prefetch.L2.global [%0], %1;" ::"l"(g), "r"(n) : "memory"); }
__device__ __forceinline__ unsigned ld_relaxed(const unsigned* p) { unsigned v; asm volatile("ld.relaxed.gpu.global.u32 %0, [%1];" : "=r"(v) : "l"(p) : "memory"); return v; }
__device__ __forceinline__ uint2 ld_relaxed64(const void* p) { unsigned long long v; asm volatile("ld.relaxed.gpu.global.u64 %0, [%1];" : "=l"(v) : "l"(p) : "memory"); return make_uint2((uint32_t)v, (uint32_t)(v >> 32)); }
__device__ __forceinline__ void st_relaxed64(void* p, uint32_t lo, uint32_t hi) { unsigned long long v = lo | ((unsigned long long)hi << 32); asm volatile("st.relaxed.gpu.global.u64 [%0], %1;" ::"l"(p), "l"(v) : "memory"); }
__device__ __forceinline__ void st_relaxed(unsigned* p, unsigned v) { asm volatile("st.relaxed.gpu.global.u32 [%0], %1;" ::"l"(p), "r"(v) : "memory"); }
__device__ __forceinline__ void red_add(unsigned* p, unsigned v) { asm volatile("red.relaxed.gpu.global.add.u32 [%0], %1;" ::"l"(p), "r"(v) : "memory"); }
__device__ __forceinline__ uint32_t prmt(uint32_t a, uint32_t b, uint32_t s) { uint32_t o; asm("prmt.b32 %0, %1, %2, %3;" : "=r"(o) : "r"(a), "r"(b), "r"(s)); return o; }
__device__ __forceinline__ uint32_t hmul2(uint32_t a, uint32_t b) { uint32_t o; asm("mul.rn.bf16x2 %0, %1, %2;" : "=r"(o) : "r"(a), "r"(b)); return o; }
__device__ __forceinline__ uint32_t hfma2(uint32_t a, uint32_t b, uint32_t c) { uint32_t o; asm("fma.rn.bf16x2 %0, %1, %2, %3;" : "=r"(o) : "r"(a), "r"(b), "r"(c)); return o; }
__device__ __forceinline__ uint32_t shiftmul(__nv_bfloat162 wa, __nv_bfloat162 wb, uint32_t k0, uint32_t k1, uint32_t k2, uint32_t k3, uint32_t v) {
  typedef const __nv_bfloat162& R;
  __nv_bfloat162 a = __hmul2(__high2bfloat162(wb), reinterpret_cast<R>(k3));
  a = __hfma2(__low2bfloat162(wb), reinterpret_cast<R>(k2), a);
  a = __hfma2(__high2bfloat162(wa), reinterpret_cast<R>(k1), a);
  a = __hfma2(__low2bfloat162(wa), reinterpret_cast<R>(k0), a);
  a = __hmul2(a, reinterpret_cast<R>(v));
  return reinterpret_cast<const uint32_t&>(a);
}
__device__ __forceinline__ uint32_t packbf(float lo, float hi) { uint32_t o; asm("cvt.rn.bf16x2.f32 %0, %1, %2;" : "=r"(o) : "f"(hi), "f"(lo)); return o; }
__device__ __forceinline__ float bflo(uint32_t v) { return __uint_as_float(v << 16); }
__device__ __forceinline__ float bfhi(uint32_t v) { return __uint_as_float(v & 0xffff0000u); }
__device__ __forceinline__ uint64_t mkdesc(uint32_t addr, uint32_t lbo, uint32_t sbo, uint32_t sw) {
  return (uint64_t)((addr & 0x3FFFF) >> 4) | ((uint64_t)(lbo >> 4) << 16) | ((uint64_t)(sbo >> 4) << 32) | ((uint64_t)sw << 62);
}
__device__ __forceinline__ void wg_fence() { asm volatile("wgmma.fence.sync.aligned;" ::: "memory"); }
__device__ __forceinline__ void wg_commit() { asm volatile("wgmma.commit_group.sync.aligned;" ::: "memory"); }
template <int N> __device__ __forceinline__ void wg_wait() { asm volatile("wgmma.wait_group.sync.aligned %0;" ::"n"(N) : "memory"); }
__device__ __forceinline__ uint32_t xz(uint32_t v, uint32_t z) { uint32_t o; asm volatile("xor.b32 %0, %1, %2;" : "=r"(o) : "r"(v), "r"(z)); return o; }
__device__ __forceinline__ uint32_t xz3(uint32_t v, uint32_t d, uint32_t z) { uint32_t o; asm volatile("lop3.b32 %0, %1, %2, %3, 0x78;" : "=r"(o) : "r"(v), "r"(d), "r"(z)); return o; }
#define SPIN_GUARD(c) do { ++(c); asm volatile("{.reg .pred p; setp.gt.u32 p, %0, 4000000; @p trap;}" ::"r"(c)); } while (0)

template<int N> struct WRS;
template<> struct WRS<8>{ static __device__ __forceinline__ void f(float* d, uint32_t a0, uint32_t a1, uint32_t a2, uint32_t a3, uint64_t db, int sd){
  asm volatile("{.reg .pred p; setp.ne.b32 p, %9, 0;\n"
  "wgmma.mma_async.sync.aligned.m64n8k16.f32.bf16.bf16 {%0,%1,%2,%3}, {%4,%5,%6,%7}, %8, p, 1, 1, 0;}\n"
  : "+f"(d[0]),"+f"(d[1]),"+f"(d[2]),"+f"(d[3]) : "r"(a0),"r"(a1),"r"(a2),"r"(a3),"l"(db),"r"(sd)); } };
template<> struct WRS<16>{ static __device__ __forceinline__ void f(float* d, uint32_t a0, uint32_t a1, uint32_t a2, uint32_t a3, uint64_t db, int sd){
  asm volatile("{.reg .pred p; setp.ne.b32 p, %13, 0;\n"
  "wgmma.mma_async.sync.aligned.m64n16k16.f32.bf16.bf16 {%0,%1,%2,%3,%4,%5,%6,%7}, {%8,%9,%10,%11}, %12, p, 1, 1, 0;}\n"
  : "+f"(d[0]),"+f"(d[1]),"+f"(d[2]),"+f"(d[3]),"+f"(d[4]),"+f"(d[5]),"+f"(d[6]),"+f"(d[7]) : "r"(a0),"r"(a1),"r"(a2),"r"(a3),"l"(db),"r"(sd)); } };
template<> struct WRS<24>{ static __device__ __forceinline__ void f(float* d, uint32_t a0, uint32_t a1, uint32_t a2, uint32_t a3, uint64_t db, int sd){
  asm volatile("{.reg .pred p; setp.ne.b32 p, %17, 0;\n"
  "wgmma.mma_async.sync.aligned.m64n24k16.f32.bf16.bf16 {%0,%1,%2,%3,%4,%5,%6,%7,%8,%9,%10,%11}, {%12,%13,%14,%15}, %16, p, 1, 1, 0;}\n"
  : "+f"(d[0]),"+f"(d[1]),"+f"(d[2]),"+f"(d[3]),"+f"(d[4]),"+f"(d[5]),"+f"(d[6]),"+f"(d[7]),"+f"(d[8]),"+f"(d[9]),"+f"(d[10]),"+f"(d[11]) : "r"(a0),"r"(a1),"r"(a2),"r"(a3),"l"(db),"r"(sd)); } };
template<> struct WRS<32>{ static __device__ __forceinline__ void f(float* d, uint32_t a0, uint32_t a1, uint32_t a2, uint32_t a3, uint64_t db, int sd){
  asm volatile("{.reg .pred p; setp.ne.b32 p, %21, 0;\n"
  "wgmma.mma_async.sync.aligned.m64n32k16.f32.bf16.bf16 {%0,%1,%2,%3,%4,%5,%6,%7,%8,%9,%10,%11,%12,%13,%14,%15}, {%16,%17,%18,%19}, %20, p, 1, 1, 0;}\n"
  : "+f"(d[0]),"+f"(d[1]),"+f"(d[2]),"+f"(d[3]),"+f"(d[4]),"+f"(d[5]),"+f"(d[6]),"+f"(d[7]),"+f"(d[8]),"+f"(d[9]),"+f"(d[10]),"+f"(d[11]),"+f"(d[12]),"+f"(d[13]),"+f"(d[14]),"+f"(d[15]) : "r"(a0),"r"(a1),"r"(a2),"r"(a3),"l"(db),"r"(sd)); } };
template<> struct WRS<40>{ static __device__ __forceinline__ void f(float* d, uint32_t a0, uint32_t a1, uint32_t a2, uint32_t a3, uint64_t db, int sd){
  asm volatile("{.reg .pred p; setp.ne.b32 p, %25, 0;\n"
  "wgmma.mma_async.sync.aligned.m64n40k16.f32.bf16.bf16 {%0,%1,%2,%3,%4,%5,%6,%7,%8,%9,%10,%11,%12,%13,%14,%15,%16,%17,%18,%19}, {%20,%21,%22,%23}, %24, p, 1, 1, 0;}\n"
  : "+f"(d[0]),"+f"(d[1]),"+f"(d[2]),"+f"(d[3]),"+f"(d[4]),"+f"(d[5]),"+f"(d[6]),"+f"(d[7]),"+f"(d[8]),"+f"(d[9]),"+f"(d[10]),"+f"(d[11]),"+f"(d[12]),"+f"(d[13]),"+f"(d[14]),"+f"(d[15]),"+f"(d[16]),"+f"(d[17]),"+f"(d[18]),"+f"(d[19]) : "r"(a0),"r"(a1),"r"(a2),"r"(a3),"l"(db),"r"(sd)); } };
template<> struct WRS<48>{ static __device__ __forceinline__ void f(float* d, uint32_t a0, uint32_t a1, uint32_t a2, uint32_t a3, uint64_t db, int sd){
  asm volatile("{.reg .pred p; setp.ne.b32 p, %29, 0;\n"
  "wgmma.mma_async.sync.aligned.m64n48k16.f32.bf16.bf16 {%0,%1,%2,%3,%4,%5,%6,%7,%8,%9,%10,%11,%12,%13,%14,%15,%16,%17,%18,%19,%20,%21,%22,%23}, {%24,%25,%26,%27}, %28, p, 1, 1, 0;}\n"
  : "+f"(d[0]),"+f"(d[1]),"+f"(d[2]),"+f"(d[3]),"+f"(d[4]),"+f"(d[5]),"+f"(d[6]),"+f"(d[7]),"+f"(d[8]),"+f"(d[9]),"+f"(d[10]),"+f"(d[11]),"+f"(d[12]),"+f"(d[13]),"+f"(d[14]),"+f"(d[15]),"+f"(d[16]),"+f"(d[17]),"+f"(d[18]),"+f"(d[19]),"+f"(d[20]),"+f"(d[21]),"+f"(d[22]),"+f"(d[23]) : "r"(a0),"r"(a1),"r"(a2),"r"(a3),"l"(db),"r"(sd)); } };
template<> struct WRS<56>{ static __device__ __forceinline__ void f(float* d, uint32_t a0, uint32_t a1, uint32_t a2, uint32_t a3, uint64_t db, int sd){
  asm volatile("{.reg .pred p; setp.ne.b32 p, %33, 0;\n"
  "wgmma.mma_async.sync.aligned.m64n56k16.f32.bf16.bf16 {%0,%1,%2,%3,%4,%5,%6,%7,%8,%9,%10,%11,%12,%13,%14,%15,%16,%17,%18,%19,%20,%21,%22,%23,%24,%25,%26,%27}, {%28,%29,%30,%31}, %32, p, 1, 1, 0;}\n"
  : "+f"(d[0]),"+f"(d[1]),"+f"(d[2]),"+f"(d[3]),"+f"(d[4]),"+f"(d[5]),"+f"(d[6]),"+f"(d[7]),"+f"(d[8]),"+f"(d[9]),"+f"(d[10]),"+f"(d[11]),"+f"(d[12]),"+f"(d[13]),"+f"(d[14]),"+f"(d[15]),"+f"(d[16]),"+f"(d[17]),"+f"(d[18]),"+f"(d[19]),"+f"(d[20]),"+f"(d[21]),"+f"(d[22]),"+f"(d[23]),"+f"(d[24]),"+f"(d[25]),"+f"(d[26]),"+f"(d[27]) : "r"(a0),"r"(a1),"r"(a2),"r"(a3),"l"(db),"r"(sd)); } };
template<> struct WRS<64>{ static __device__ __forceinline__ void f(float* d, uint32_t a0, uint32_t a1, uint32_t a2, uint32_t a3, uint64_t db, int sd){
  asm volatile("{.reg .pred p; setp.ne.b32 p, %37, 0;\n"
  "wgmma.mma_async.sync.aligned.m64n64k16.f32.bf16.bf16 {%0,%1,%2,%3,%4,%5,%6,%7,%8,%9,%10,%11,%12,%13,%14,%15,%16,%17,%18,%19,%20,%21,%22,%23,%24,%25,%26,%27,%28,%29,%30,%31}, {%32,%33,%34,%35}, %36, p, 1, 1, 0;}\n"
  : "+f"(d[0]),"+f"(d[1]),"+f"(d[2]),"+f"(d[3]),"+f"(d[4]),"+f"(d[5]),"+f"(d[6]),"+f"(d[7]),"+f"(d[8]),"+f"(d[9]),"+f"(d[10]),"+f"(d[11]),"+f"(d[12]),"+f"(d[13]),"+f"(d[14]),"+f"(d[15]),"+f"(d[16]),"+f"(d[17]),"+f"(d[18]),"+f"(d[19]),"+f"(d[20]),"+f"(d[21]),"+f"(d[22]),"+f"(d[23]),"+f"(d[24]),"+f"(d[25]),"+f"(d[26]),"+f"(d[27]),"+f"(d[28]),"+f"(d[29]),"+f"(d[30]),"+f"(d[31]) : "r"(a0),"r"(a1),"r"(a2),"r"(a3),"l"(db),"r"(sd)); } };
template<> struct WRS<72>{ static __device__ __forceinline__ void f(float* d, uint32_t a0, uint32_t a1, uint32_t a2, uint32_t a3, uint64_t db, int sd){
  asm volatile("{.reg .pred p; setp.ne.b32 p, %41, 0;\n"
  "wgmma.mma_async.sync.aligned.m64n72k16.f32.bf16.bf16 {%0,%1,%2,%3,%4,%5,%6,%7,%8,%9,%10,%11,%12,%13,%14,%15,%16,%17,%18,%19,%20,%21,%22,%23,%24,%25,%26,%27,%28,%29,%30,%31,%32,%33,%34,%35}, {%36,%37,%38,%39}, %40, p, 1, 1, 0;}\n"
  : "+f"(d[0]),"+f"(d[1]),"+f"(d[2]),"+f"(d[3]),"+f"(d[4]),"+f"(d[5]),"+f"(d[6]),"+f"(d[7]),"+f"(d[8]),"+f"(d[9]),"+f"(d[10]),"+f"(d[11]),"+f"(d[12]),"+f"(d[13]),"+f"(d[14]),"+f"(d[15]),"+f"(d[16]),"+f"(d[17]),"+f"(d[18]),"+f"(d[19]),"+f"(d[20]),"+f"(d[21]),"+f"(d[22]),"+f"(d[23]),"+f"(d[24]),"+f"(d[25]),"+f"(d[26]),"+f"(d[27]),"+f"(d[28]),"+f"(d[29]),"+f"(d[30]),"+f"(d[31]),"+f"(d[32]),"+f"(d[33]),"+f"(d[34]),"+f"(d[35]) : "r"(a0),"r"(a1),"r"(a2),"r"(a3),"l"(db),"r"(sd)); } };
template<> struct WRS<80>{ static __device__ __forceinline__ void f(float* d, uint32_t a0, uint32_t a1, uint32_t a2, uint32_t a3, uint64_t db, int sd){
  asm volatile("{.reg .pred p; setp.ne.b32 p, %45, 0;\n"
  "wgmma.mma_async.sync.aligned.m64n80k16.f32.bf16.bf16 {%0,%1,%2,%3,%4,%5,%6,%7,%8,%9,%10,%11,%12,%13,%14,%15,%16,%17,%18,%19,%20,%21,%22,%23,%24,%25,%26,%27,%28,%29,%30,%31,%32,%33,%34,%35,%36,%37,%38,%39}, {%40,%41,%42,%43}, %44, p, 1, 1, 0;}\n"
  : "+f"(d[0]),"+f"(d[1]),"+f"(d[2]),"+f"(d[3]),"+f"(d[4]),"+f"(d[5]),"+f"(d[6]),"+f"(d[7]),"+f"(d[8]),"+f"(d[9]),"+f"(d[10]),"+f"(d[11]),"+f"(d[12]),"+f"(d[13]),"+f"(d[14]),"+f"(d[15]),"+f"(d[16]),"+f"(d[17]),"+f"(d[18]),"+f"(d[19]),"+f"(d[20]),"+f"(d[21]),"+f"(d[22]),"+f"(d[23]),"+f"(d[24]),"+f"(d[25]),"+f"(d[26]),"+f"(d[27]),"+f"(d[28]),"+f"(d[29]),"+f"(d[30]),"+f"(d[31]),"+f"(d[32]),"+f"(d[33]),"+f"(d[34]),"+f"(d[35]),"+f"(d[36]),"+f"(d[37]),"+f"(d[38]),"+f"(d[39]) : "r"(a0),"r"(a1),"r"(a2),"r"(a3),"l"(db),"r"(sd)); } };
template<> struct WRS<88>{ static __device__ __forceinline__ void f(float* d, uint32_t a0, uint32_t a1, uint32_t a2, uint32_t a3, uint64_t db, int sd){
  asm volatile("{.reg .pred p; setp.ne.b32 p, %49, 0;\n"
  "wgmma.mma_async.sync.aligned.m64n88k16.f32.bf16.bf16 {%0,%1,%2,%3,%4,%5,%6,%7,%8,%9,%10,%11,%12,%13,%14,%15,%16,%17,%18,%19,%20,%21,%22,%23,%24,%25,%26,%27,%28,%29,%30,%31,%32,%33,%34,%35,%36,%37,%38,%39,%40,%41,%42,%43}, {%44,%45,%46,%47}, %48, p, 1, 1, 0;}\n"
  : "+f"(d[0]),"+f"(d[1]),"+f"(d[2]),"+f"(d[3]),"+f"(d[4]),"+f"(d[5]),"+f"(d[6]),"+f"(d[7]),"+f"(d[8]),"+f"(d[9]),"+f"(d[10]),"+f"(d[11]),"+f"(d[12]),"+f"(d[13]),"+f"(d[14]),"+f"(d[15]),"+f"(d[16]),"+f"(d[17]),"+f"(d[18]),"+f"(d[19]),"+f"(d[20]),"+f"(d[21]),"+f"(d[22]),"+f"(d[23]),"+f"(d[24]),"+f"(d[25]),"+f"(d[26]),"+f"(d[27]),"+f"(d[28]),"+f"(d[29]),"+f"(d[30]),"+f"(d[31]),"+f"(d[32]),"+f"(d[33]),"+f"(d[34]),"+f"(d[35]),"+f"(d[36]),"+f"(d[37]),"+f"(d[38]),"+f"(d[39]),"+f"(d[40]),"+f"(d[41]),"+f"(d[42]),"+f"(d[43]) : "r"(a0),"r"(a1),"r"(a2),"r"(a3),"l"(db),"r"(sd)); } };
template<> struct WRS<96>{ static __device__ __forceinline__ void f(float* d, uint32_t a0, uint32_t a1, uint32_t a2, uint32_t a3, uint64_t db, int sd){
  asm volatile("{.reg .pred p; setp.ne.b32 p, %53, 0;\n"
  "wgmma.mma_async.sync.aligned.m64n96k16.f32.bf16.bf16 {%0,%1,%2,%3,%4,%5,%6,%7,%8,%9,%10,%11,%12,%13,%14,%15,%16,%17,%18,%19,%20,%21,%22,%23,%24,%25,%26,%27,%28,%29,%30,%31,%32,%33,%34,%35,%36,%37,%38,%39,%40,%41,%42,%43,%44,%45,%46,%47}, {%48,%49,%50,%51}, %52, p, 1, 1, 0;}\n"
  : "+f"(d[0]),"+f"(d[1]),"+f"(d[2]),"+f"(d[3]),"+f"(d[4]),"+f"(d[5]),"+f"(d[6]),"+f"(d[7]),"+f"(d[8]),"+f"(d[9]),"+f"(d[10]),"+f"(d[11]),"+f"(d[12]),"+f"(d[13]),"+f"(d[14]),"+f"(d[15]),"+f"(d[16]),"+f"(d[17]),"+f"(d[18]),"+f"(d[19]),"+f"(d[20]),"+f"(d[21]),"+f"(d[22]),"+f"(d[23]),"+f"(d[24]),"+f"(d[25]),"+f"(d[26]),"+f"(d[27]),"+f"(d[28]),"+f"(d[29]),"+f"(d[30]),"+f"(d[31]),"+f"(d[32]),"+f"(d[33]),"+f"(d[34]),"+f"(d[35]),"+f"(d[36]),"+f"(d[37]),"+f"(d[38]),"+f"(d[39]),"+f"(d[40]),"+f"(d[41]),"+f"(d[42]),"+f"(d[43]),"+f"(d[44]),"+f"(d[45]),"+f"(d[46]),"+f"(d[47]) : "r"(a0),"r"(a1),"r"(a2),"r"(a3),"l"(db),"r"(sd)); } };
template<> struct WRS<104>{ static __device__ __forceinline__ void f(float* d, uint32_t a0, uint32_t a1, uint32_t a2, uint32_t a3, uint64_t db, int sd){
  asm volatile("{.reg .pred p; setp.ne.b32 p, %57, 0;\n"
  "wgmma.mma_async.sync.aligned.m64n104k16.f32.bf16.bf16 {%0,%1,%2,%3,%4,%5,%6,%7,%8,%9,%10,%11,%12,%13,%14,%15,%16,%17,%18,%19,%20,%21,%22,%23,%24,%25,%26,%27,%28,%29,%30,%31,%32,%33,%34,%35,%36,%37,%38,%39,%40,%41,%42,%43,%44,%45,%46,%47,%48,%49,%50,%51}, {%52,%53,%54,%55}, %56, p, 1, 1, 0;}\n"
  : "+f"(d[0]),"+f"(d[1]),"+f"(d[2]),"+f"(d[3]),"+f"(d[4]),"+f"(d[5]),"+f"(d[6]),"+f"(d[7]),"+f"(d[8]),"+f"(d[9]),"+f"(d[10]),"+f"(d[11]),"+f"(d[12]),"+f"(d[13]),"+f"(d[14]),"+f"(d[15]),"+f"(d[16]),"+f"(d[17]),"+f"(d[18]),"+f"(d[19]),"+f"(d[20]),"+f"(d[21]),"+f"(d[22]),"+f"(d[23]),"+f"(d[24]),"+f"(d[25]),"+f"(d[26]),"+f"(d[27]),"+f"(d[28]),"+f"(d[29]),"+f"(d[30]),"+f"(d[31]),"+f"(d[32]),"+f"(d[33]),"+f"(d[34]),"+f"(d[35]),"+f"(d[36]),"+f"(d[37]),"+f"(d[38]),"+f"(d[39]),"+f"(d[40]),"+f"(d[41]),"+f"(d[42]),"+f"(d[43]),"+f"(d[44]),"+f"(d[45]),"+f"(d[46]),"+f"(d[47]),"+f"(d[48]),"+f"(d[49]),"+f"(d[50]),"+f"(d[51]) : "r"(a0),"r"(a1),"r"(a2),"r"(a3),"l"(db),"r"(sd)); } };
template<> struct WRS<112>{ static __device__ __forceinline__ void f(float* d, uint32_t a0, uint32_t a1, uint32_t a2, uint32_t a3, uint64_t db, int sd){
  asm volatile("{.reg .pred p; setp.ne.b32 p, %61, 0;\n"
  "wgmma.mma_async.sync.aligned.m64n112k16.f32.bf16.bf16 {%0,%1,%2,%3,%4,%5,%6,%7,%8,%9,%10,%11,%12,%13,%14,%15,%16,%17,%18,%19,%20,%21,%22,%23,%24,%25,%26,%27,%28,%29,%30,%31,%32,%33,%34,%35,%36,%37,%38,%39,%40,%41,%42,%43,%44,%45,%46,%47,%48,%49,%50,%51,%52,%53,%54,%55}, {%56,%57,%58,%59}, %60, p, 1, 1, 0;}\n"
  : "+f"(d[0]),"+f"(d[1]),"+f"(d[2]),"+f"(d[3]),"+f"(d[4]),"+f"(d[5]),"+f"(d[6]),"+f"(d[7]),"+f"(d[8]),"+f"(d[9]),"+f"(d[10]),"+f"(d[11]),"+f"(d[12]),"+f"(d[13]),"+f"(d[14]),"+f"(d[15]),"+f"(d[16]),"+f"(d[17]),"+f"(d[18]),"+f"(d[19]),"+f"(d[20]),"+f"(d[21]),"+f"(d[22]),"+f"(d[23]),"+f"(d[24]),"+f"(d[25]),"+f"(d[26]),"+f"(d[27]),"+f"(d[28]),"+f"(d[29]),"+f"(d[30]),"+f"(d[31]),"+f"(d[32]),"+f"(d[33]),"+f"(d[34]),"+f"(d[35]),"+f"(d[36]),"+f"(d[37]),"+f"(d[38]),"+f"(d[39]),"+f"(d[40]),"+f"(d[41]),"+f"(d[42]),"+f"(d[43]),"+f"(d[44]),"+f"(d[45]),"+f"(d[46]),"+f"(d[47]),"+f"(d[48]),"+f"(d[49]),"+f"(d[50]),"+f"(d[51]),"+f"(d[52]),"+f"(d[53]),"+f"(d[54]),"+f"(d[55]) : "r"(a0),"r"(a1),"r"(a2),"r"(a3),"l"(db),"r"(sd)); } };
template<> struct WRS<120>{ static __device__ __forceinline__ void f(float* d, uint32_t a0, uint32_t a1, uint32_t a2, uint32_t a3, uint64_t db, int sd){
  asm volatile("{.reg .pred p; setp.ne.b32 p, %65, 0;\n"
  "wgmma.mma_async.sync.aligned.m64n120k16.f32.bf16.bf16 {%0,%1,%2,%3,%4,%5,%6,%7,%8,%9,%10,%11,%12,%13,%14,%15,%16,%17,%18,%19,%20,%21,%22,%23,%24,%25,%26,%27,%28,%29,%30,%31,%32,%33,%34,%35,%36,%37,%38,%39,%40,%41,%42,%43,%44,%45,%46,%47,%48,%49,%50,%51,%52,%53,%54,%55,%56,%57,%58,%59}, {%60,%61,%62,%63}, %64, p, 1, 1, 0;}\n"
  : "+f"(d[0]),"+f"(d[1]),"+f"(d[2]),"+f"(d[3]),"+f"(d[4]),"+f"(d[5]),"+f"(d[6]),"+f"(d[7]),"+f"(d[8]),"+f"(d[9]),"+f"(d[10]),"+f"(d[11]),"+f"(d[12]),"+f"(d[13]),"+f"(d[14]),"+f"(d[15]),"+f"(d[16]),"+f"(d[17]),"+f"(d[18]),"+f"(d[19]),"+f"(d[20]),"+f"(d[21]),"+f"(d[22]),"+f"(d[23]),"+f"(d[24]),"+f"(d[25]),"+f"(d[26]),"+f"(d[27]),"+f"(d[28]),"+f"(d[29]),"+f"(d[30]),"+f"(d[31]),"+f"(d[32]),"+f"(d[33]),"+f"(d[34]),"+f"(d[35]),"+f"(d[36]),"+f"(d[37]),"+f"(d[38]),"+f"(d[39]),"+f"(d[40]),"+f"(d[41]),"+f"(d[42]),"+f"(d[43]),"+f"(d[44]),"+f"(d[45]),"+f"(d[46]),"+f"(d[47]),"+f"(d[48]),"+f"(d[49]),"+f"(d[50]),"+f"(d[51]),"+f"(d[52]),"+f"(d[53]),"+f"(d[54]),"+f"(d[55]),"+f"(d[56]),"+f"(d[57]),"+f"(d[58]),"+f"(d[59]) : "r"(a0),"r"(a1),"r"(a2),"r"(a3),"l"(db),"r"(sd)); } };
template<> struct WRS<128>{ static __device__ __forceinline__ void f(float* d, uint32_t a0, uint32_t a1, uint32_t a2, uint32_t a3, uint64_t db, int sd){
  asm volatile("{.reg .pred p; setp.ne.b32 p, %69, 0;\n"
  "wgmma.mma_async.sync.aligned.m64n128k16.f32.bf16.bf16 {%0,%1,%2,%3,%4,%5,%6,%7,%8,%9,%10,%11,%12,%13,%14,%15,%16,%17,%18,%19,%20,%21,%22,%23,%24,%25,%26,%27,%28,%29,%30,%31,%32,%33,%34,%35,%36,%37,%38,%39,%40,%41,%42,%43,%44,%45,%46,%47,%48,%49,%50,%51,%52,%53,%54,%55,%56,%57,%58,%59,%60,%61,%62,%63}, {%64,%65,%66,%67}, %68, p, 1, 1, 0;}\n"
  : "+f"(d[0]),"+f"(d[1]),"+f"(d[2]),"+f"(d[3]),"+f"(d[4]),"+f"(d[5]),"+f"(d[6]),"+f"(d[7]),"+f"(d[8]),"+f"(d[9]),"+f"(d[10]),"+f"(d[11]),"+f"(d[12]),"+f"(d[13]),"+f"(d[14]),"+f"(d[15]),"+f"(d[16]),"+f"(d[17]),"+f"(d[18]),"+f"(d[19]),"+f"(d[20]),"+f"(d[21]),"+f"(d[22]),"+f"(d[23]),"+f"(d[24]),"+f"(d[25]),"+f"(d[26]),"+f"(d[27]),"+f"(d[28]),"+f"(d[29]),"+f"(d[30]),"+f"(d[31]),"+f"(d[32]),"+f"(d[33]),"+f"(d[34]),"+f"(d[35]),"+f"(d[36]),"+f"(d[37]),"+f"(d[38]),"+f"(d[39]),"+f"(d[40]),"+f"(d[41]),"+f"(d[42]),"+f"(d[43]),"+f"(d[44]),"+f"(d[45]),"+f"(d[46]),"+f"(d[47]),"+f"(d[48]),"+f"(d[49]),"+f"(d[50]),"+f"(d[51]),"+f"(d[52]),"+f"(d[53]),"+f"(d[54]),"+f"(d[55]),"+f"(d[56]),"+f"(d[57]),"+f"(d[58]),"+f"(d[59]),"+f"(d[60]),"+f"(d[61]),"+f"(d[62]),"+f"(d[63]) : "r"(a0),"r"(a1),"r"(a2),"r"(a3),"l"(db),"r"(sd)); } };
__device__ __forceinline__ void wgmma_ss_n128_ta1_tb1(float* d, uint32_t da, uint32_t db, int sd){
  asm volatile("{.reg .pred p; .reg .b64 a, b; setp.ne.b32 p, %66, 0; mov.b64 a, {%64, 0x40000040}; mov.b64 b, {%65, 0x40000040};\n"
  "wgmma.mma_async.sync.aligned.m64n128k16.f32.bf16.bf16 {%0,%1,%2,%3,%4,%5,%6,%7,%8,%9,%10,%11,%12,%13,%14,%15,%16,%17,%18,%19,%20,%21,%22,%23,%24,%25,%26,%27,%28,%29,%30,%31,%32,%33,%34,%35,%36,%37,%38,%39,%40,%41,%42,%43,%44,%45,%46,%47,%48,%49,%50,%51,%52,%53,%54,%55,%56,%57,%58,%59,%60,%61,%62,%63}, a, b, p, 1, 1, 1, 1;}\n"
  : "+f"(d[0]),"+f"(d[1]),"+f"(d[2]),"+f"(d[3]),"+f"(d[4]),"+f"(d[5]),"+f"(d[6]),"+f"(d[7]),"+f"(d[8]),"+f"(d[9]),"+f"(d[10]),"+f"(d[11]),"+f"(d[12]),"+f"(d[13]),"+f"(d[14]),"+f"(d[15]),"+f"(d[16]),"+f"(d[17]),"+f"(d[18]),"+f"(d[19]),"+f"(d[20]),"+f"(d[21]),"+f"(d[22]),"+f"(d[23]),"+f"(d[24]),"+f"(d[25]),"+f"(d[26]),"+f"(d[27]),"+f"(d[28]),"+f"(d[29]),"+f"(d[30]),"+f"(d[31]),"+f"(d[32]),"+f"(d[33]),"+f"(d[34]),"+f"(d[35]),"+f"(d[36]),"+f"(d[37]),"+f"(d[38]),"+f"(d[39]),"+f"(d[40]),"+f"(d[41]),"+f"(d[42]),"+f"(d[43]),"+f"(d[44]),"+f"(d[45]),"+f"(d[46]),"+f"(d[47]),"+f"(d[48]),"+f"(d[49]),"+f"(d[50]),"+f"(d[51]),"+f"(d[52]),"+f"(d[53]),"+f"(d[54]),"+f"(d[55]),"+f"(d[56]),"+f"(d[57]),"+f"(d[58]),"+f"(d[59]),"+f"(d[60]),"+f"(d[61]),"+f"(d[62]),"+f"(d[63]) : "r"(da),"r"(db),"r"(sd)); }
__device__ __forceinline__ void wgmma_ss_n80_ta0_tb1(float* d, uint32_t da, uint32_t db, int sd){
  asm volatile("{.reg .pred p; .reg .b64 a, b; setp.ne.b32 p, %42, 0; mov.b64 a, {%40, 0x40}; mov.b64 b, {%41, 0x8};\n"
  "wgmma.mma_async.sync.aligned.m64n80k16.f32.bf16.bf16 {%0,%1,%2,%3,%4,%5,%6,%7,%8,%9,%10,%11,%12,%13,%14,%15,%16,%17,%18,%19,%20,%21,%22,%23,%24,%25,%26,%27,%28,%29,%30,%31,%32,%33,%34,%35,%36,%37,%38,%39}, a, b, p, 1, 1, 0, 1;}\n"
  : "+f"(d[0]),"+f"(d[1]),"+f"(d[2]),"+f"(d[3]),"+f"(d[4]),"+f"(d[5]),"+f"(d[6]),"+f"(d[7]),"+f"(d[8]),"+f"(d[9]),"+f"(d[10]),"+f"(d[11]),"+f"(d[12]),"+f"(d[13]),"+f"(d[14]),"+f"(d[15]),"+f"(d[16]),"+f"(d[17]),"+f"(d[18]),"+f"(d[19]),"+f"(d[20]),"+f"(d[21]),"+f"(d[22]),"+f"(d[23]),"+f"(d[24]),"+f"(d[25]),"+f"(d[26]),"+f"(d[27]),"+f"(d[28]),"+f"(d[29]),"+f"(d[30]),"+f"(d[31]),"+f"(d[32]),"+f"(d[33]),"+f"(d[34]),"+f"(d[35]),"+f"(d[36]),"+f"(d[37]),"+f"(d[38]),"+f"(d[39]) : "r"(da),"r"(db),"r"(sd)); }
__device__ __forceinline__ void wgmma_ss_n160_ta0_tb1(float* d, uint32_t da, uint32_t db, int sd){
  asm volatile("{.reg .pred p; .reg .b64 a, b; setp.ne.b32 p, %82, 0; mov.b64 a, {%80, 0x40}; mov.b64 b, {%81, 0x8};\n"
  "wgmma.mma_async.sync.aligned.m64n160k16.f32.bf16.bf16 {%0,%1,%2,%3,%4,%5,%6,%7,%8,%9,%10,%11,%12,%13,%14,%15,%16,%17,%18,%19,%20,%21,%22,%23,%24,%25,%26,%27,%28,%29,%30,%31,%32,%33,%34,%35,%36,%37,%38,%39,%40,%41,%42,%43,%44,%45,%46,%47,%48,%49,%50,%51,%52,%53,%54,%55,%56,%57,%58,%59,%60,%61,%62,%63,%64,%65,%66,%67,%68,%69,%70,%71,%72,%73,%74,%75,%76,%77,%78,%79}, a, b, p, 1, 1, 0, 1;}\n"
  : "+f"(d[0]),"+f"(d[1]),"+f"(d[2]),"+f"(d[3]),"+f"(d[4]),"+f"(d[5]),"+f"(d[6]),"+f"(d[7]),"+f"(d[8]),"+f"(d[9]),"+f"(d[10]),"+f"(d[11]),"+f"(d[12]),"+f"(d[13]),"+f"(d[14]),"+f"(d[15]),"+f"(d[16]),"+f"(d[17]),"+f"(d[18]),"+f"(d[19]),"+f"(d[20]),"+f"(d[21]),"+f"(d[22]),"+f"(d[23]),"+f"(d[24]),"+f"(d[25]),"+f"(d[26]),"+f"(d[27]),"+f"(d[28]),"+f"(d[29]),"+f"(d[30]),"+f"(d[31]),"+f"(d[32]),"+f"(d[33]),"+f"(d[34]),"+f"(d[35]),"+f"(d[36]),"+f"(d[37]),"+f"(d[38]),"+f"(d[39]),"+f"(d[40]),"+f"(d[41]),"+f"(d[42]),"+f"(d[43]),"+f"(d[44]),"+f"(d[45]),"+f"(d[46]),"+f"(d[47]),"+f"(d[48]),"+f"(d[49]),"+f"(d[50]),"+f"(d[51]),"+f"(d[52]),"+f"(d[53]),"+f"(d[54]),"+f"(d[55]),"+f"(d[56]),"+f"(d[57]),"+f"(d[58]),"+f"(d[59]),"+f"(d[60]),"+f"(d[61]),"+f"(d[62]),"+f"(d[63]),"+f"(d[64]),"+f"(d[65]),"+f"(d[66]),"+f"(d[67]),"+f"(d[68]),"+f"(d[69]),"+f"(d[70]),"+f"(d[71]),"+f"(d[72]),"+f"(d[73]),"+f"(d[74]),"+f"(d[75]),"+f"(d[76]),"+f"(d[77]),"+f"(d[78]),"+f"(d[79]) : "r"(da),"r"(db),"r"(sd)); }

struct Strm { uint32_t n0, n1; };
struct AW { uint32_t c0, n0, c1, n1; };
struct ConvCtx { uint32_t sb, ea, eb, ec, ed, pa, pc, z; uint64_t da, db, dc; bool l0; };
__host__ __device__ constexpr int st_S(int n) { return n < 34 ? ((n & 1) ? 2 : 0) : 1; }
__host__ __device__ constexpr int st_I(int n) { return n < 34 ? n / 2 : n - 34; }
template <int N>
__device__ __forceinline__ void load_aw(AW& w, const ConvCtx& x) {
  constexpr int S = st_S(N), I = st_I(N);
  constexpr uint32_t o = (S == 1 ? 2 * ECH : 0) + 2 * I * REC;
  if (S == 0) mbar_wait_u(x.sb + B_ERDY + 8 * I, 0);
  const uint32_t ea = S == 2 ? x.ec : x.ea, eb = S == 2 ? x.ed : x.eb;
  w.c0 = lds32(ea + o); w.c1 = lds32(eb + o); w.n0 = lds32(ea + o + REC); w.n1 = lds32(eb + o + REC);
}
template <int N> struct Step {
  static __device__ __forceinline__ void run(float* a, float* b, float* c, Strm* st, AW& w, const ConvCtx& x) {
    constexpr int S = st_S(N), I = st_I(N), HALF = S == 2, J = (I > 0) ? I - 1 : 0;
    float* acc = S == 0 ? a : (S == 1 ? b : c);
    if (N == 34) mbar_wait_u(x.sb + B_KFL, 0);
    if (N == 34) mbar_wait_u(x.sb + B_EDONE, 0);
    if (I > 0) wg_wait<(N < 33) ? 1 : 0>();
    constexpr bool dump = (I > 0) && (!HALF || (I & 1) == 0);
    constexpr int DS = HALF ? (J / 2) : J;
    if (I < 16) {
      constexpr int F = HALF ? ((I & 15) / 2) : (I & 15);
      constexpr int NR = HALF ? 32 : 64;
      if (dump) {
#pragma unroll
        for (int r = 4 * F; r < NR; r++) { float nv; asm volatile("mov.f32 %0, %1;" : "=f"(nv) : "f"(acc[r])); acc[r] = nv; }
      }
      uint32_t c0 = w.c0, n0 = w.n0, c1 = w.c1, n1 = w.n1, p0, p1, e0, e1;
      if (I > 0) {
        const uint32_t dep = __float_as_uint(acc[dump ? 4 * DS : 4 * F]);
        p0 = xz(st[S].n0, x.z); p1 = xz(st[S].n1, x.z); e0 = xz3(c0, dep, x.z); e1 = xz3(c1, dep, x.z);
      } else { p0 = xz3(x.z, c0, x.z); p1 = xz3(x.z, c1, x.z); e0 = xz(c0, x.z); e1 = xz(c1, x.z); }
      if (N < 49) load_aw<N == 31 ? 34 : (N < 49 ? N + 1 : 0)>(w, x);
      asm volatile("wgmma.fence.sync.aligned;" : "+r"(p0), "+r"(p1), "+r"(e0), "+r"(e1), "+r"(c0), "+r"(c1), "+r"(n0), "+r"(n1)::"memory");
      const uint64_t d = (S == 0 ? x.da : (S == 1 ? x.db : x.dc)) - (HALF ? (I & 1) * 16 : 0);
      WRS<2 * NR - 8 * F>::f(acc + 4 * F, c0, n0, p0, e0, d, I > 0);
      WRS<2 * NR - 8 * F>::f(acc + 4 * F, c1, n1, p1, e1, d - 1, 1);
      st[S].n0 = n0; st[S].n1 = n1;
      wg_commit();
    }
    if (dump) stsm2t((HALF ? x.pc : x.pa) + (HALF ? 2 * DS : DS) * 256, packbf(acc[4 * DS], acc[4 * DS + 1]), packbf(acc[4 * DS + 2], acc[4 * DS + 3]));
    if (S != 0 && I >= 4 && (I & (S == 1 ? 7 : 3)) == 0) { fence_async_s(); __syncwarp(); if (x.l0) mbar_arrive(x.sb + B_YRDY + 2 * (I >= 4 ? I - 4 : 0)); }
    if (S != 0 && (I & 3) == 0) STAMP0(72 + I / 4 + (S == 1 ? 5 : 0));
    Step<N + 1>::run(a, b, c, st, w, x);
  }
};
template <> struct Step<51> { static __device__ __forceinline__ void run(float*, float*, float*, Strm*, AW&, const ConvCtx&) {} };

struct EpiCtx { float n0, n1, m0, m1; uint32_t cs; unsigned char* gp; };
__device__ __forceinline__ float swiglu(float ag, float au, float mu, float n, float cg, float cu) {
  const float dg = fmaf(-mu, cg, ag), du = fmaf(-mu, cu, au);
  float t; asm("tanh.approx.f32 %0, %1;" : "=f"(t) : "f"(dg * n));
  const float p = dg * du;
  return fmaf(p, t, p);
}
template <int P, int J>
__device__ __forceinline__ void epi_piece(const float* acc, const EpiCtx& e, float4 c) {
  const float g0 = swiglu(acc[4 * J], acc[32 + 4 * J], e.m0, e.n0, c.x, c.z);
  const float g1 = swiglu(acc[4 * J + 1], acc[33 + 4 * J], e.m0, e.n0, c.y, c.w);
  const float g2 = swiglu(acc[4 * J + 2], acc[34 + 4 * J], e.m1, e.n1, c.x, c.z);
  const float g3 = swiglu(acc[4 * J + 3], acc[35 + 4 * J], e.m1, e.n1, c.y, c.w);
  *reinterpret_cast<uint32_t*>(e.gp + P * 16384 + J * 128) = packbf(g0, g1);
  *reinterpret_cast<uint32_t*>(e.gp + P * 16384 + J * 128 + 1024) = packbf(g2, g3);
}
__host__ __device__ constexpr int g1_pass(int s) { return s < 6 ? 0 : (s < 6 + XE ? 1 : (s < 10 + XE ? 0 : (s < 20 ? 1 : 2))); }
__host__ __device__ constexpr int g1_kb(int s) { return s < 6 ? s : (s < 6 + XE ? s - 6 : (s < 10 + XE ? s - XE : s % 10)); }
__host__ __device__ constexpr int pieces_before(int s) {
  return s <= E0S ? 0 : (s <= 20 ? (8 * (s - E0S)) / (20 - E0S) : (s >= 28 ? 16 : s - 12));
}
template <int S> struct G1 {
  static __device__ __forceinline__ void run(float* acc0, float* acc1, float* acc2, uint32_t sb, uint32_t da, uint32_t dw, bool l0, EpiCtx& e, uint32_t st2, float4* cs2) {
    constexpr int P = g1_pass(S), KB = g1_kb(S), J0 = pieces_before(S), J1 = pieces_before(S + 1);
    if (P == 0) mbar_wait_u(sb + B_AFULL + 8 * KB, 1);
    mbar_wait_u(sb + B_WFULL + 8 * (S & 3), (S >> 2) & 1);
    if (S == 0) STAMP0(3);
    wg_fence();
#pragma unroll
    for (int k = 0; k < 4; k++) wgmma_ss_n128_ta1_tb1(P == 0 ? acc0 : (P == 1 ? acc1 : acc2), da + KB * 1024 + k * 128, dw + (S & 3) * 1024 + k * 128, (KB > 0 || k > 0));
    wg_commit();
    wg_wait<1>();
    if (l0 && S > 0) { mbar_arrive(sb + B_WEMPTY + 8 * ((S + 3) & 3)); if (S > 20) mbar_arrive(sb + B_AEMPTY + 8 * (KB > 0 ? KB - 1 : 0)); }
    if (S == INCS && CR < 216) asm volatile("setmaxnreg.inc.sync.aligned.u32 216;");
    if (S == E0S) {
      mbar_wait_u(sb + B_S2, 0);
      const float2 a = lds64f(st2), b = lds64f(st2 + 64);
      e.n0 = a.x * NSCALE; e.m0 = a.y; e.n1 = b.x * NSCALE; e.m1 = b.y;
    }
    if (S == E0S || S == 20) mbar_wait_u(sb + B_CS + (S == 20 ? 8 : 0), 0);
    if (J1 > J0) {
      const float4 c = lds128f(e.cs + J0 * 64);
      if (J1 > J0 + 1) { const float4 c2 = lds128f(e.cs + J0 * 64 + 64); epi_piece<J0 / 8, (J0 + 1) & 7>(J0 < 8 ? acc0 : acc1, e, c2); }
      epi_piece<J0 / 8, J0 & 7>(J0 < 8 ? acc0 : acc1, e, c);
      if ((J1 & 7) == 0) bar_arrive(3 + J0 / 8, J0 < 8 ? PUB0 : 288);
    }
    if (S == 22) mbar_wait_u(sb + B_CS + 16, 0);
    if (S >= 22) cs2[(S + 2) & 7] = lds128f(e.cs + 1024 + ((S + 2) & 7) * 64);
    if (G2STAMP == 1) STAMP0(84 + S + (S >= 10 ? 6 : 0));
    if (S == 9 || S == 19) STAMP0(S == 9 ? 4 : 5);
    G1<S + 1>::run(acc0, acc1, acc2, sb, da, dw, l0, e, st2, cs2);
  }
};
template <> struct G1<30> { static __device__ __forceinline__ void run(float*, float*, float*, uint32_t, uint32_t, uint32_t, bool, EpiCtx&, uint32_t, float4*) {} };

__host__ __device__ constexpr int g2_slot(int t) { return t < 32 ? t / 3 : (t + 32) / 6; }
__host__ __device__ constexpr int g2_blk(int t) { return t < 32 ? t / 4 : 8 + ((t - 32) & 15) / 4; }
__host__ __device__ constexpr int w2_buf(int s) { return (s % 6) < 4 ? 2 + (((s % 6) + 2) & 3) : (s % 6) - 4; }
__host__ __device__ constexpr uint32_t w2_full(int s) { return w2_buf(s) < 2 ? B_AFULL + 64 + 8 * w2_buf(s) : B_WFULL + 8 * (w2_buf(s) - 2); }
__host__ __device__ constexpr uint32_t w2_empty(int s) { return w2_buf(s) < 2 ? B_AEMPTY + 64 + 8 * w2_buf(s) : B_WEMPTY + 8 * (w2_buf(s) - 2); }
__host__ __device__ constexpr uint32_t w2_fpar(int s) { return ((s / 6) + ((s % 6) < 2 ? 1 : 0)) & 1; }
template <int T0, int T1>
__device__ __forceinline__ void g2_issue(float* o, uint32_t sb, uint32_t dg, uint32_t dwa, uint32_t dwb) {
#pragma unroll
  for (int t = T0; t < T1; t++) {
    if (t < 48 && (t & 3) == 0) mbar_wait_u(sb + B_AFULL + 8 * (g2_blk(t) & 7), g2_blk(t) >> 3);
    if (t == 0 || g2_slot(t) != g2_slot(t - 1)) mbar_wait_u(sb + w2_full(g2_slot(t)), w2_fpar(g2_slot(t)));
  }
  wg_fence();
#pragma unroll
  for (int t = T0; t < T1; t++) {
    const uint32_t a = dg + (g2_blk(t) & 7) * 1024 + (t & 3) * 16, w = w2_buf(g2_slot(t)) * 1024;
    if (t < 32) {
      wgmma_ss_n160_ta0_tb1(o, a, dwa + w + (t % 3) * 320, t > 0);
    }
    else wgmma_ss_n80_ta0_tb1(o + (t < 48 ? 0 : 40), a, dwb + w + ((t + 32) % 6) * 160, 1);
  }
  wg_commit();
}
template <int T0, int T1>
__device__ __forceinline__ void g2_release(uint32_t sb, bool l0) {
  if (l0) {
#pragma unroll
    for (int t = T0; t < T1; t++) {
      if (g2_slot(t) != g2_slot(t + 1) && g2_slot(t) < 10) mbar_arrive(sb + w2_empty(g2_slot(t)));
      if ((t < 16 && (t & 3) == 3) || t == 31) mbar_arrive(sb + B_AEMPTY + 8 * (t >> 2));
    }
  }
}
template <int T, int TE, int G> struct G2 {
  static __device__ __forceinline__ void run(float* o, uint32_t sb, uint32_t dg, uint32_t dwa, uint32_t dwb, bool l0) {
    g2_issue<T, T + G>(o, sb, dg, dwa, dwb);
    wg_wait<1>();
    g2_release<T - G, T>(sb, l0);
    if (G2STAMP == 2) STAMP0(99 + T / 3);
    G2<T + G, TE, G>::run(o, sb, dg, dwa, dwb, l0);
  }
};
template <int TE, int G> struct G2<TE, TE, G> { static __device__ __forceinline__ void run(float*, uint32_t, uint32_t, uint32_t, uint32_t, bool) {} };

__device__ __forceinline__ void wgmma_ss_n8(float* d, uint32_t da, uint32_t db, int sd) {
  asm volatile("{.reg .pred p; .reg .b64 a, b; setp.ne.b32 p, %6, 0; mov.b64 a, {%4, 8}; mov.b64 b, {%5, 8};\n"
               "wgmma.mma_async.sync.aligned.m64n8k16.f32.bf16.bf16 {%0,%1,%2,%3}, a, b, p, 1, 1, 0, 0;}\n"
               : "+f"(d[0]), "+f"(d[1]), "+f"(d[2]), "+f"(d[3]) : "r"(da), "r"(db), "r"(sd));
}
__device__ __forceinline__ void wgmma_ss_n8_ta(float* d, uint64_t da, uint64_t db) {
  asm volatile("{.reg .pred p; setp.eq.b32 p, 0, 0;\nwgmma.mma_async.sync.aligned.m64n8k16.f32.bf16.bf16 {%0,%1,%2,%3}, %4, %5, p, 1, 1, 1, 0;}\n"
               : "+f"(d[0]), "+f"(d[1]), "+f"(d[2]), "+f"(d[3]) : "l"(da), "l"(db));
}
__device__ __forceinline__ void ld_stats(float4& sa, float4& sc, const float2* p) {
  asm volatile("ld.relaxed.gpu.global.v4.f32 {%0,%1,%2,%3}, [%4];" : "=f"(sa.x), "=f"(sa.y), "=f"(sa.z), "=f"(sa.w) : "l"(p) : "memory");
  asm volatile("ld.relaxed.gpu.global.v4.f32 {%0,%1,%2,%3}, [%4];" : "=f"(sc.x), "=f"(sc.y), "=f"(sc.z), "=f"(sc.w) : "l"(p + 64) : "memory");
}
__device__ __forceinline__ void check_stats(float4& a, float4& c, const float2* p, uint32_t tag) {
  unsigned n = 0;
  while (!__all_sync(0xffffffff, (((__float_as_uint(a.x) ^ tag) | (__float_as_uint(a.z) ^ tag) | (__float_as_uint(c.x) ^ tag) | (__float_as_uint(c.z) ^ tag)) & 3) == 0)) {
    SPIN_GUARD(n); __nanosleep(100); ld_stats(a, c, p);
  }
}
__device__ __forceinline__ void red_sum(float* y, uint32_t da, uint32_t db) {
  wgmma_ss_n8(y, da, db, 0);
  wgmma_ss_n8(y, da + (2 * PR - 64) / 16, db, 1);
}
__device__ __forceinline__ void red_fin(uint32_t* hp, const float* y, uint32_t xl, uint32_t xh, const float4& sa, const float4& sc) {
  const float x0 = bflo(xl), x1 = bfhi(xl), x2 = bflo(xh), x3 = bfhi(xh);
  hp[0] = packbf(x0 + (x0 * sa.x - sa.y) * y[0], x1 + (x1 * sa.z - sa.w) * y[1]);
  hp[32] = packbf(x2 + (x2 * sc.x - sc.y) * y[2], x3 + (x3 * sc.z - sc.w) * y[3]);
}
__device__ __forceinline__ void fetch_colsum(uint32_t sb, int f, int p, int lane, unsigned tag) {
  const void* src = g_colsum + (f * 3 + p) * 128 + lane * 4;
  uint4 u; unsigned c = 0;
  for (;;) {
    asm volatile("ld.relaxed.gpu.global.v4.u32 {%0,%1,%2,%3}, [%4];" : "=r"(u.x), "=r"(u.y), "=r"(u.z), "=r"(u.w) : "l"(src) : "memory");
    if (__all_sync(0xffffffff, (((u.x ^ tag) | (u.y ^ tag) | (u.z ^ tag) | (u.w ^ tag)) & 3) == 0)) break;
    SPIN_GUARD(c);
    __nanosleep(200);
  }
  sts128(sb + OFF_CS + p * 512 + lane * 16, u);
  __syncwarp();
  if (lane == 0) mbar_arrive(sb + B_CS + 8 * p);
  STAMP(29 + p);
}
__device__ __forceinline__ uint32_t eoff(uint32_t i) { const uint32_t q = (i >> 2) & 3; return (4 * q + ((i >> 4) ^ (q & 2))) * 16 + (i & 3) * 4; }
__device__ __forceinline__ int logical_id() {
  int cta; asm volatile("mov.u32 %0, %%ctaid.x;" : "=r"(cta));
  const int c = cta >> 1, q7 = ((c - 36) * 37) >> 8;
  const int m = c < 4 ? 15 : (c < 36 ? (c - 4) & 7 : c - 28 - 7 * q7), qi = c < 4 ? c : (c < 36 ? (c - 4) >> 3 : q7);
  return 8 * m + 2 * qi + (cta & 1);
}

struct Maps { CUtensorMap h, hr, w1, w3, w2, c[2][5]; };
struct Params {
  const __nv_bfloat16 *kf, *k, *v, *x, *shift, *D, *w2;
  __nv_bfloat16* out;
  uint32_t z;
};

__device__ __forceinline__ void patch_tap0(uint32_t sb, uint32_t off, int c0, int n, uint32_t bin, uint32_t bout, int lane) {
  const int lid = logical_id();
  mbar_wait(sb + bin, 0);
  if (lane < n) {
    const uint32_t a = sb + off + lane * KS, k0 = lds32(a), i = 5 * lid + c0 + lane - ((5 * (lid & ~1)) & ~7);
    const uint32_t dw = lds32(sb + OFF_D + (i >> 1) * 4);
    sts32(a, prmt(packbf(bflo(k0) + ((i & 1) ? bfhi(dw) : bflo(dw)), 0.f), k0, 0x7610));
  }
  fence_async_s();
  __syncwarp();
  if (lane == 0) mbar_arrive(sb + bout);
}
__device__ __forceinline__ void issue_task(const Maps& tm, uint32_t sb, int lid, int n, uint32_t sl) {
  const int G0 = (5 * (lid & ~1)) >> 3;
  const bool wide = (G0 & 3) != 3;
  const CUtensorMap* mp = tm.c[wide ? 1 : 0];
  const uint32_t d = sb + slot_off(sl), b = sb + B_TFULL + 8 * sl;
  const int c0 = (wide ? (G0 & ~3) : G0) * 8, t0 = 16 * n + 8 * (lid & 1);
  tma4d(d, mp, c0, t0, 0, b);
  tma4d(d + 8192, mp + 1, c0, t0, 0, b);
  tma4d(d + 24576, mp + 3, c0, t0 - 1, 6, b);
  tma4d(d + 24832, mp + 4, c0, t0 - 1, 6, b);
  tma4d(d + 16384, mp + 2, c0, t0, 0, b);
  mbar_expect(b, wide ? 25088 : 12544);
}

__global__ void __cluster_dims__(2, 1, 1) __launch_bounds__(512, 1)
h3_ffn_kernel(const __grid_constant__ Params pr, const __grid_constant__ Maps tm) {
  extern __shared__ __align__(1024) unsigned char smem[];
  STAMP0(127);
  if (threadIdx.x == 480 && blockIdx.x < 128) {
    prefetch_l2(pr.k + blockIdx.x * 1280, 2560); prefetch_l2(pr.v + blockIdx.x * 1280, 2560);
    prefetch_l2(pr.kf + blockIdx.x * 10240, 12288); prefetch_l2(pr.x + blockIdx.x * 1280, 2560);
    prefetch_l2(pr.k + 163840 + blockIdx.x * 1280, 2560); prefetch_l2(pr.v + 163840 + blockIdx.x * 1280, 2560);
    prefetch_l2(pr.x + 163840 + blockIdx.x * 1280, 2560);
  }
  const uint32_t sb = (uint32_t)__cvta_generic_to_shared(smem);
  const int wsel = __shfl_sync(0xffffffff, threadIdx.x >> 5, 0), wgsel = wsel >> 2;
  const int cta = blockIdx.x;
  if (cta < 128) {
    {
      if (wsel == 0) {
        const int lid = logical_id();
        if (elect1()) {
          mbar_init(sb + B_TFULL + 8, 1); mbar_init(sb + B_TFULL + 16, 1);
          mbar_init(sb + B_KF0, 1); mbar_init(sb + B_KF0 + 8, 1); mbar_init(sb + B_KF, 1);
#pragma unroll 1
          for (int n = 0; n < 2; n++) {
            if (n == ((((5 * (lid & ~1)) >> 3) & 3) == 3 ? KFPOSH : KFPOS)) {
              const int G8 = (5 * (lid & ~1)) & ~7;
              bulk_g2s(sb + OFF_SH, pr.shift + 4 * G8, 128, sb + B_KF0 + 8);
              bulk_g2s(sb + OFF_D, pr.D + G8, 32, sb + B_KF0);
#pragma unroll
              for (int c = 0; c < 3; c++) bulk_g2s(sb + OFF_KFE + c * KS, pr.kf + (5 * lid + c) * 2048, 4096, sb + B_KF0);
              mbar_expect(sb + B_KF0 + 8, 128);
              mbar_expect(sb + B_KF0, 3 * 4096 + 32);
            }
            issue_task(tm, sb, lid, n, 1 + n);
          }
        }
        __syncwarp();
        STAMP(13);
      }
      if (wsel == 1 && elect1()) {
#pragma unroll
        for (int i = 0; i < 16; i++) mbar_init(sb + B_ERDY + 8 * i, 1);
        asm volatile("fence.mbarrier_init.release.cluster;" ::: "memory");
#pragma unroll
        for (int i = 0; i < 8; i++) mbar_expect(sb + B_ERDY + 16 * i + 8 * ((cta & 1) ^ 1), 2 * REC);
      }
      if (wsel == 3 && elect1()) {
#pragma unroll
        for (int i = 0; i < 10; i++) if (i != 1 && i != 2) mbar_init(sb + B_AFULL + 8 * i, 1);
#pragma unroll
        for (int i = 0; i < 10; i++) if (i != 1 && i != 2) mbar_arrive(sb + B_AFULL + 8 * i);
      }
      if (wsel == 2 && elect1()) {
#pragma unroll
        for (int i = 0; i < 4; i++) {
          mbar_init(sb + B_YRDY + 8 * i, 8); mbar_init(sb + B_S2 + 8 * i, i ? 1 : 4);
          mbar_init(sb + B_WFULL + 8 * i, 1); mbar_init(sb + B_WEMPTY + 8 * i, 8);
        }
#pragma unroll
        for (int i = 0; i < 10; i++) mbar_init(sb + B_AEMPTY + 8 * i, 8);
        mbar_init(sb + B_CDONE, 4); mbar_init(sb + B_EP, 1); mbar_init(sb + B_XFREE, 8); mbar_init(sb + B_XIN, 1);
        asm volatile("fence.mbarrier_init.release.cluster;" ::: "memory");
        mbar_expect(sb + B_XIN, 20480);
        mbar_init(sb + B_W2G, 2); mbar_init(sb + B_EDONE, 8); mbar_init(sb + B_KFL0, 1); mbar_init(sb + B_KFL, 1);
      }
      if (wgsel == 1) {
        const int t = threadIdx.x & 127;
        const uint4 zero = make_uint4(0, 0, 0, 0);
        if (t < 120) {
          sts128(sb + OFF_U - REC + t * 16, zero);
          if (t < 112) sts128(sb + OFF_P + (t >> 3) * PR + (t & 7) * 16, zero);
          if (t < 26) sts128(sb + OFF_KFE - 16 + (t < 24 ? -16 * t : (t - 23) * KS), zero);
          if (t < 32) sts32(sb + OFF_ID + 4 * t, (t & 3) == (t >> 3) ? (0x3f80u << (4 * (t & 4))) : 0u);
        }
        fence_async_s();
      }
      __syncwarp();
      cl_arrive_rlx();
      bar_sync(0, 512);
      STAMP0(12);
    }
  }
#define ROLE_IDS const int tid = tid_x(), lane = tid & 31, warp = __shfl_sync(0xffffffff, tid >> 5, 0), wg = warp >> 2, w4 = warp & 3; (void)wg; (void)w4; (void)lane;

  if (cta >= 128) {
    ROLE_IDS
    const uint32_t bf = sb + OFF_MISC, be = bf + 96;
    if (warp == 0 && elect1()) {
#pragma unroll
      for (int i = 0; i < 12; i++) { mbar_init(bf + 8 * i, 1); mbar_init(be + 8 * i, 4); }
    }
    if (warp == 1) { sts32(sb + OFF_MISC + 512 + 4 * lane, 0x3f803f80u); fence_async_s(); }
    const unsigned t0 = clock();
    const unsigned tag = (ld_relaxed(&g_done) / NCTA + 1) & 3;
    __syncthreads();
    if (wg < 2) {
      const int f = 2 * (cta - 128) + wg;
      const uint64_t db = mkdesc(sb + OFF_MISC + 512, 0, 128, 0);
      uint32_t sl = wg, ph = 0, rel = 0;
#pragma unroll 1
      for (int p = 0; p < 3; p++) {
        float ag[4] = {0.f, 0.f, 0.f, 0.f}, au[4] = {0.f, 0.f, 0.f, 0.f};
#pragma unroll 1
        for (int kb = 0; kb < 10; kb++) {
          mbar_wait(bf + 8 * sl, ph);
          wg_fence();
          const uint64_t dw = mkdesc(sb + sl * 16384, 8192, 1024, 1);
#pragma unroll
          for (int k = 0; k < 4; k++) { wgmma_ss_n8_ta(ag, dw + k * 128, db); wgmma_ss_n8_ta(au, dw + 512 + k * 128, db); }
          wg_commit();
          wg_wait<1>();
          if (lane == 0 && kb > 0) mbar_arrive(be + 8 * rel);
          rel = sl;
          sl += 2; if (sl >= 12) { sl -= 12; ph ^= 1; }
        }
        wg_wait<0>();
        if (lane == 0) mbar_arrive(be + 8 * rel);
        const int g = lane >> 2, t = lane & 3;
        const float v = (t & 1) ? ((t & 2) ? au[2] : au[0]) : ((t & 2) ? ag[2] : ag[0]);
        st_relaxed(reinterpret_cast<unsigned*>(g_colsum) + (f * 3 + p) * 128 + 16 * (2 * w4 + (t >> 1)) + 4 * (g >> 1) + 2 * (t & 1) + (g & 1),
                   (__float_as_uint(v) & ~3u) | tag);
      }
    } else if (warp == 10) {
      if (elect1()) {
        while ((int)(clock() - t0) < W2PF_DELAY) {}
#pragma unroll 1
        for (int i = 0; i < (W2PF_DELAY ? 30 : 0); i++) prefetch_l2((const unsigned char*)pr.w2 + ((cta - 128) * 30 + i) * 16384, 16384);
      }
    } else if (warp < 10) {
      if (elect1()) {
        while ((int)(clock() - t0) < AUX_DELAY) {}
        uint32_t sl = w4, ph = 1;
        int c0 = 192 * (2 * (cta - 128) + w4), r0 = 0;
#pragma unroll 1
        for (int s = 0; s < 30; s++) {
          mbar_wait(be + 8 * sl, ph);
          tma3d(sb + sl * 16384, &tm.w1, c0, r0, bf + 8 * sl);
          tma3d(sb + sl * 16384 + 8192, &tm.w3, c0, r0, bf + 8 * sl);
          mbar_expect(bf + 8 * sl, 16384);
          sl += 2; if (sl >= 12) { sl -= 12; ph ^= 1; }
          if (++r0 == 10) { r0 = 0; c0 += 64; }
        }
      }
    }
    __syncthreads();
    STAMP0(0);
    if (tid == 0) red_add(&g_done, 1);
    return;
  }

  if (wgsel < 2) {
    ROLE_IDS
    asm volatile("setmaxnreg.inc.sync.aligned.u32 %0;" ::"n"(CR));
    cl_wait();
    STAMP0(10);
    {
      float a[64], b[64], c[32];
      Strm st[3];
      ConvCtx x;
      const int g = lane >> 2, t = lane & 3;
      x.sb = sb; x.z = pr.z; x.l0 = lane == 0;
      const int i0 = 16 * w4 + g - 2 * t;
      x.ec = sb + OFF_U + (i0 < 0 ? -(int)REC : 0) + eoff(i0 & 63); x.ed = sb + OFF_U + eoff(i0 + 8);
      x.ea = x.ec + (1 + wg) * ECH; x.eb = x.ed + (1 + wg) * ECH;
      x.pa = sb + OFF_P + (4 + warp) * PR + 128 + 16 * (lane & 15);
      x.pc = sb + OFF_P + w4 * PR + 128 + wg * 256 + 16 * (lane & 15);
      x.da = mkdesc(sb + OFF_KFE + (1 + wg) * KS, 128, 256, 0);
      x.db = mkdesc(sb + OFF_KFL + wg * KS, 128, 256, 0);
      x.dc = mkdesc(sb + OFF_KFE + wg * 256, 128, 512, 0);
      if (warp == 7) patch_tap0(sb, OFF_KFE, 0, 3, B_KF0, B_KF, lane);
      mbar_wait(sb + B_KF, 0);
      if (MSTART) mbar_wait(sb + B_ERDY + 8 * MSTART, 0);
      STAMP0(1);
      AW aw;
      load_aw<0>(aw, x);
      Step<0>::run(a, b, c, st, aw, x);
      STAMP0(2);
    }
    const int tid2 = tid_x(), ln = tid2 & 31;
    const int wp = __shfl_sync(0xffffffff, tid2 >> 5, 0), wgi = wp >> 2, wq = wp & 3;
    const bool l0 = ln == 0;
    const int lid = logical_id(), m = TILE_M(lid), f = TILE_F(lid);
    EpiCtx e;
    e.cs = sb + OFF_CS + (ln & 3) * 16;
    e.gp = g_g + (size_t)(m * 24 + 3 * f) * 16384 + wp * 2048 + ln * 4;
    const uint32_t st2 = sb + OFF_ST2 + (wp * 16 + (ln >> 2)) * 8;
    const uint32_t da = (uint32_t)mkdesc(sb + OFF_A + wgi * 8192, 8192, 1024, 1), dw = (uint32_t)mkdesc(sb + OFF_W, 8192, 1024, 1);
    float acc0[64], acc1[64], acc2[64];
    float4 cs2[8];
    G1<0>::run(acc0, acc1, acc2, sb, da, dw, l0, e, st2, cs2);
    STAMP0(6);
    float o[80];
    const uint32_t dg = da ^ ((uint32_t)mkdesc(0, 8192, 0, 0) ^ (uint32_t)mkdesc(0, 128, 0, 0));
    const uint32_t dwa = (uint32_t)mkdesc(sb + OFF_W - 32768, 2560, 128, 0), dwb = (uint32_t)mkdesc(sb + OFF_W - 32768, 1280, 128, 0);
    g2_issue<0, 3>(o, sb, dg, dwa, dwb);
    wg_wait<1>();
    if (l0) { mbar_arrive(sb + B_WEMPTY + 8 * 1); mbar_arrive(sb + B_AEMPTY + 8 * 9); }
    g2_issue<3, 6>(o, sb, dg, dwa, dwb);
    STAMP0(96);
    epi_piece<2, 0>(acc2, e, cs2[0]); epi_piece<2, 1>(acc2, e, cs2[1]); epi_piece<2, 2>(acc2, e, cs2[2]); epi_piece<2, 3>(acc2, e, cs2[3]);
    wg_wait<1>();
    g2_release<0, 3>(sb, l0);
    g2_issue<6, 9>(o, sb, dg, dwa, dwb);
    epi_piece<2, 4>(acc2, e, cs2[4]); epi_piece<2, 5>(acc2, e, cs2[5]); epi_piece<2, 6>(acc2, e, cs2[6]); epi_piece<2, 7>(acc2, e, cs2[7]);
    bar_arrive(5, 288);
    STAMP0(7);
    wg_wait<1>();
    g2_release<3, 6>(sb, l0);
    G2<9, 30, 3>::run(o, sb, dg, dwa, dwb, l0);
    const uint32_t peer = mapa(sb, (logical_id() & 1) ^ 1);
    if (l0) asm volatile("mbarrier.arrive.relaxed.cluster.shared::cluster.b64 _, [%0];" ::"r"(peer + B_XFREE) : "memory");
    g2_issue<30, 32>(o, sb, dg, dwa, dwb);
    wg_wait<0>();
    g2_release<27, 32>(sb, l0);
    STAMP0(97);
#pragma unroll
    for (int r = 0; r < 80; r++) { float nv; asm volatile("mov.f32 %0, %1;" : "=f"(nv) : "f"(o[r])); o[r] = nv; }
    g2_issue<32, 36>(o, sb, dg, dwa, dwb);
    G2<36, 52, 4>::run(o, sb, dg, dwa, dwb, l0);
    STAMP0(98);
    g2_issue<52, 56>(o, sb, dg, dwa, dwb);
    {
      const int t4 = tid_x();
      const uint32_t xd = peer + OFF_A + 4 * 16384 + (t4 >> 5) * 2560 + (t4 & 31) * 16;
      mbar_wait_u(sb + B_XFREE, 0);
#pragma unroll
      for (int j = 0; j < 5; j++)
        st_async4(xd + j * 512, packbf(o[8 * j], o[8 * j + 1]), packbf(o[8 * j + 2], o[8 * j + 3]), packbf(o[8 * j + 4], o[8 * j + 5]),
                  packbf(o[8 * j + 6], o[8 * j + 7]), peer + B_XIN);
    }
    if (G2STAMP == 2) STAMP0(117);
    g2_issue<56, 64>(o, sb, dg, dwa, dwb);
    if (G2STAMP == 2) STAMP0(118);
    uint4 xin[5];
    const int t5 = tid_x(), lid5 = logical_id();
    uint32_t hres[20];
    mbar_wait_u(sb + B_AFULL + 56, 1);
#pragma unroll
    for (int j = 0; j < 5; j++)
      ldsm4t(sb + OFF_A + 4 * 16384 + 20480 + (t5 >> 7) * 10240 + (16 * j + ((t5 >> 1) & 8) + (t5 & 7)) * 128 + (((((t5 >> 4) & 6) + ((t5 >> 3) & 1)) ^ (t5 & 7)) << 4),
             hres[4 * j], hres[4 * j + 1], hres[4 * j + 2], hres[4 * j + 3]);
    {
      const int ln = t5 & 31, wp = t5 >> 5;
      const uint32_t stg = sb + OFF_A + 4 * 16384 + 40960 + wp * 2816;
      uint32_t sa = stg + (ln & 15) * 176 + (ln >> 4) * 16, xi = sb + OFF_A + 4 * 16384 + wp * 2560 + ln * 16, la[5], go[5];
#pragma unroll
      for (int i = 0; i < 5; i++) {
        const int idx = i * 32 + ln, row = (idx * 205) >> 11, c = idx - row * 10;
        la[i] = stg + row * 176 + c * 16; go[i] = row * 1280 + c * 16;
        asm volatile("" : "+r"(la[i]), "+r"(go[i]));
      }
      unsigned char* op = reinterpret_cast<unsigned char*>(pr.out + (128 * TILE_M(lid5) + 16 * wp) * 640 + 80 * TILE_F(lid5));
      const float r20 = e.n0 * e.n0 * RSCALE, r21 = e.n1 * e.n1 * RSCALE;
      float u[40];
#pragma unroll
      for (int i = 0; i < 20; i++) { u[2 * i] = bflo(hres[i]); u[2 * i + 1] = bfhi(hres[i]); asm volatile("" : "+f"(u[2 * i]), "+f"(u[2 * i + 1])); }
      asm volatile("" : "+r"(sa), "+r"(xi), "+l"(op));
      wg_wait<0>();
      STAMP0(8);
#pragma unroll
      for (int i = 0; i < 40; i++) { u[i] = fmaf(o[40 + i], (i & 2) ? r21 : r20, u[i]); asm volatile("" : "+f"(u[i])); }
      mbar_wait(sb + B_XIN, 0);
      if (G2STAMP == 2) STAMP0(119);
#pragma unroll
      for (int j = 0; j < 5; j++) xin[j] = lds128(xi + j * 512);
#pragma unroll
      for (int j = 0; j < 5; j++)
        stsm4(sa + j * 32, packbf(fmaf(bflo(xin[j].x), r20, u[8 * j]), fmaf(bfhi(xin[j].x), r20, u[8 * j + 1])),
              packbf(fmaf(bflo(xin[j].y), r21, u[8 * j + 2]), fmaf(bfhi(xin[j].y), r21, u[8 * j + 3])),
              packbf(fmaf(bflo(xin[j].z), r20, u[8 * j + 4]), fmaf(bfhi(xin[j].z), r20, u[8 * j + 5])),
              packbf(fmaf(bflo(xin[j].w), r21, u[8 * j + 6]), fmaf(bfhi(xin[j].w), r21, u[8 * j + 7])));
      __syncwarp();
#pragma unroll
      for (int i = 0; i < 5; i++) xin[i] = lds128(la[i]);
#pragma unroll
      for (int i = 0; i < 5; i++) stg128(op + go[i], xin[i]);
    }
    STAMP0(9);
    if (t5 == 0) red_add(&g_done, 1);
  } else {
    asm volatile("setmaxnreg.dec.sync.aligned.u32 %0;" ::"n"(256 - CR));
    float4 na, nc;
    if (wgsel == 2) {
    ROLE_IDS
    {
      const int lid = logical_id(), rank = lid & 1, c10 = 5 * (lid - rank), G0 = c10 >> 3, hh = w4 & 1;
      const bool wide = (G0 & 3) != 3;
      const int lc = (G0 + hh) * 8 + (lane >> 2) - c10;
      const bool valid = (unsigned)lc < 10u;
      if (w4 == 1 && elect1()) {
        issue_task(tm, sb, lid, 2, 0);
#pragma unroll 1
        for (int n = 3; n < 3 + KVPF; n++) { prefetch_l2(pr.k + 163840 * n + lid * 1280, 2560); prefetch_l2(pr.v + 163840 * n + lid * 1280, 2560); }
      }
      __syncwarp();
      const uint32_t T = (w4 & 2) * 2 + ((lane & 7) >> 1), bb = 1 - (lane & 1), mi = lane >> 3, ch16 = wide ? (G0 & 3) + hh : hh;
      const uint32_t pitch = wide ? 64 : 32, ssh = wide ? 0 : 1;
      const uint32_t la_rev = (16 * mi + 2 * T + bb) * pitch + ((ch16 ^ ((T & 3) >> ssh)) << 4);
      const uint32_t jj = mi ? 1 : 0, isv = mi >> 1;
      const uint32_t la_halo = T ? isv * 8192 + (16 * (6 + jj) + 2 * (T - 1) + bb) * pitch + ((ch16 ^ (((T - 1) & 3) >> ssh)) << 4)
                                 : 24576 + isv * 256 + (2 * jj + bb) * pitch + ((ch16 ^ (wide ? 2 * isv + jj : 0)) << 4);
      const bool own = (lc >= 5 ? 1 : 0) == rank;
      const uint32_t dc = lc >= 5 ? lc - 5 : lc, dx1 = 5 * ECH - dc * (ECH - 64);
      uint32_t de = sb + (w4 >> 1) * REC + dc * ECH + 16 * (lane & 3) + (own ? OFF_U + 2 * rank * REC : OFF_OUT);
      const uint32_t peer = mapa(sb, rank ^ 1);
      const CUtensorMap* mp = tm.c[wide ? 1 : 0] + (w4 - 1);
      const int c0 = (wide ? (G0 & ~3) : G0) * 8, t0 = 48 + 8 * rank;
      mbar_wait(sb + B_KF0 + 8, 0);
      const uint2 wsh = lds64(sb + OFF_SH + hh * 64 + (lane >> 2) * 8);
      const __nv_bfloat162 wa = *reinterpret_cast<const __nv_bfloat162*>(&wsh.x), wb = *reinterpret_cast<const __nv_bfloat162*>(&wsh.y);
      cl_wait();
      uint32_t sl = 1, ph = 0;
#pragma unroll 1
      for (int n = 0; n < 8; n++) {
        const uint32_t pl = sb + slot_off(sl);
        if (n >= (w4 ? 4 : 2)) mbar_wait(sb + B_ERDY + 16 * (n - 2) + 8 * (rank ^ 1), 0);
        mbar_wait(sb + B_TFULL + 8 * sl, ph);
        if (w4 == 3) STAMP(64 + n);
        if (n == 7 && w4) ld_stats(na, nc, g_stat1 + 128 * (12 + w4) + 2 * lane);
        uint32_t pm2, pp, vm1, dummy, kk[8], vv[8];
        uint4 xa, xb;
        ldsm4t(pl + 16384 + (la_rev ^ pitch), xa.x, xa.y, xa.z, xa.w);
        ldsm4t(pl + 16384 + (la_rev ^ pitch) + 64 * pitch, xb.x, xb.y, xb.z, xb.w);
        ldsm4t(pl + la_halo, pm2, pp, vm1, dummy);
        ldsm4t(pl + la_rev, kk[0], kk[1], kk[2], kk[3]);
        ldsm4t(pl + 8192 + la_rev, vv[0], vv[1], vv[2], vv[3]);
        ldsm4t(pl + la_rev + 64 * pitch, kk[4], kk[5], kk[6], kk[7]);
        ldsm4t(pl + 8192 + la_rev + 64 * pitch, vv[4], vv[5], vv[6], vv[7]);
        if (valid) { sts128(de + 256, xa); sts128(de + dx1, xb); }
        uint32_t qp = prmt(pp, pm2, 0x5432);
        uint32_t up = shiftmul(wa, wb, pp, qp, pm2, prmt(pm2, pm2, 0x3232), vm1);
#pragma unroll
        for (int j = 0; j < 8; j++) {
          const uint32_t qc = prmt(kk[j], pp, 0x5432);
          const uint32_t uc = shiftmul(wa, wb, kk[j], qc, pp, qp, vv[j]);
          pp = kk[j]; qp = qc;
          kk[j] = prmt(uc, up, 0x5432); vv[j] = uc; up = uc;
          if ((j & 1) && valid) sts128((j >= 4 ? de ^ 32 : de) + (j >> 1) * 64, make_uint4(kk[j - 1], vv[j - 1], kk[j], vv[j]));
        }
        de += own ? 4 * REC : (n == 3 ? 0u - 6 * REC : 2 * REC);
        bar_sync(2, 128);
        if (w4 == 0) {
          if (elect1()) {
            mbar_arrive(sb + B_ERDY + 16 * n + 8 * rank);
            fence_async_s();
            asm volatile("cp.async.bulk.shared::cluster.shared::cta.mbarrier::complete_tx::bytes [%0], [%1], %2, [%3];"
                         ::"r"(peer + OFF_U + (4 * n + 2 * rank) * REC), "r"(sb + OFF_OUT + (n & 3) * 2 * REC), "r"(2 * REC),
                           "r"(peer + B_ERDY + 16 * n + 8 * rank) : "memory");
          }
          __syncwarp();
        } else if (n < 5) {
          if (elect1()) {
            const uint32_t b = sb + B_TFULL + 8 * sl;
            tma4d(pl + (w4 - 1) * 8192, mp, c0, 16 * n + t0, 0, b);
            if (w4 < 3) tma4d(pl + 24320 + w4 * 256, mp + 3, c0, 16 * n + t0 - 1, 6, b);
            else mbar_expect(b, wide ? 25088 : 12544);
          }
          __syncwarp();
        }
        if (++sl == 3) { sl = 0; ph ^= 1; }
      }
      if (w4 == 0) ld_stats(na, nc, g_stat1 + 128 * 12 + 2 * lane);
      if (w4 && elect1()) {
        tma3d(sb + OFF_W + (w4 - 1) * 16384, &tm.w1, 192 * TILE_F(lid), w4 - 1, sb + B_WFULL + 8 * (w4 - 1));
        tma3d(sb + OFF_W + (w4 - 1) * 16384 + 8192, &tm.w3, 192 * TILE_F(lid), w4 - 1, sb + B_WFULL + 8 * (w4 - 1));
        mbar_expect(sb + B_WFULL + 8 * (w4 - 1), 16384);
      }
      __syncwarp();
    }
    } else {
    ROLE_IDS
    {
      const int lid = logical_id();
      const int row0 = 128 * (w4 + (lane >> 4) * 4) + lid;
      const uint4* xr = reinterpret_cast<const uint4*>(pr.x + row0 * 640) + (lane & 15);
      const unsigned dn = ld_relaxed(&g_done);
      uint4 xv[5];
#pragma unroll
      for (int q = 0; q < 5; q++) xv[q] = ldg128(xr + q * 16);
      if (w4 == 3 && elect1()) { prefetch_tm(&tm.w1); prefetch_tm(&tm.w3); prefetch_tm(&tm.h); prefetch_tm(&tm.hr); prefetch_tm(&tm.w2); }
      __syncwarp();
      cl_wait();
      const unsigned tag = (dn / NCTA + 1) & 3;
      if (tid == 384) { sts32(sb + OFF_EP, dn / NCTA + 1); mbar_arrive(sb + B_EP); }
#pragma unroll 1
      for (int h = 0; h < 2; h++) {
        const float pv = bflo(__shfl_sync(0xffffffff, xv[0].x, lane & 16));
        float s0 = 0.f, q0 = 0.f, s1 = 0.f, q1 = 0.f;
#pragma unroll
        for (int q = 0; q < 5; q++) {
          float a = bflo(xv[q].x) - pv, b = bfhi(xv[q].x) - pv;
          s0 += a + b; q0 = fmaf(a, a, fmaf(b, b, q0));
          a = bflo(xv[q].y) - pv; b = bfhi(xv[q].y) - pv;
          s1 += a + b; q1 = fmaf(a, a, fmaf(b, b, q1));
          a = bflo(xv[q].z) - pv; b = bfhi(xv[q].z) - pv;
          s0 += a + b; q0 = fmaf(a, a, fmaf(b, b, q0));
          a = bflo(xv[q].w) - pv; b = bfhi(xv[q].w) - pv;
          s1 += a + b; q1 = fmaf(a, a, fmaf(b, b, q1));
        }
        s0 += s1; q0 += q1;
        asm volatile("" : "+f"(s0), "+f"(q0));
        if (h == 0) {
#pragma unroll
          for (int q = 0; q < 5; q++) xv[q] = ldg128(xr + 1024 * 80 + q * 16);
        }
        const bool o1 = lane & 1;
        float v = (o1 ? q0 : s0) + __shfl_xor_sync(0xffffffff, o1 ? s0 : q0, 1);
#pragma unroll
        for (int o = 8; o > 1; o >>= 1) v += __shfl_xor_sync(0xffffffff, v, o);
        const float dm = v * (1.f / 640.f), e2 = __shfl_xor_sync(0xffffffff, dm, 1);
        const float r = rsqrtf(fmaxf(e2 - dm * dm, 0.f) + LN_EPS);
        if ((lane & 15) == 0) st_relaxed64(&g_stat1[1024 * h + row0], (__float_as_uint(r) & ~3u) | tag, __float_as_uint((pv + dm) * r));
        if (h == 0 && w4 == 1 && elect1()) {
#pragma unroll
          for (int c = 0; c < 2; c++) bulk_g2s(sb + OFF_KFL + c * KS, pr.kf + (5 * lid + 3 + c) * 2048, 4096, sb + B_KFL0);
          mbar_expect(sb + B_KFL0, 2 * 4096);
        }
        __syncwarp();
        if (w4 == 0) STAMP(118 + h);
      }
      ld_stats(na, nc, g_stat1 + 128 * w4 + 2 * lane);
    }
    }
    {
      ROLE_IDS
      const int q0 = wg == 2 ? 3 : 0;
      const uint32_t db = (uint32_t)mkdesc(sb + OFF_ID, 0, 128, 0), da = (uint32_t)mkdesc(sb + OFF_P + 128, PR - 32, 128, 0), xs = (lane & 4) ? 64 : ECH;
      const uint32_t xa = sb + OFF_U + 2 * REC * w4 + ((lane & 4) ? 5 * ECH : 256) + 16 * (lane >> 3) + 4 * (lane & 3);
      uint32_t* hp = reinterpret_cast<uint32_t*>(g_hT) + logical_id() * 1024 + 64 * w4 + lane;
      const float2* sp = g_stat1 + 128 * w4 + 2 * lane;
      mbar_wait(sb + B_EP, 0);
      const uint32_t tag = lds32(sb + OFF_EP);
#pragma unroll 1
      for (int q = q0; q < (wg == 2 ? 4 : 3); q++) {
        if (q == 1 && w4 == 1) { mbar_wait(sb + B_KF0, 0); patch_tap0(sb, OFF_KFL, 3, 2, B_KFL0, B_KFL, lane); }
        check_stats(na, nc, sp + 512 * q, tag);
        const float4 sa = na, sc = nc;
        if (q < 3) ld_stats(na, nc, sp + 512 * (q + 1));
        float y[3][4];
        uint32_t xl[3], xh[3];
        mbar_wait(sb + B_YRDY + 8 * q, 0);
        wg_fence();
#pragma unroll
        for (int i = 0; i < 3; i++) red_sum(y[i], da + q * 64 + i * (4 * PR / 16), db);
        wg_commit();
#pragma unroll
        for (int i = 0; i < 3; i++) { xl[i] = lds32(xa + q * 8 * REC + i * xs); xh[i] = lds32(xa + q * 8 * REC + i * xs + REC); }
        wg_wait<0>();
#pragma unroll
        for (int i = 0; i < 3; i++) red_fin(hp + q * 256 + i * 131072, y[i], xl[i], xh[i], sa, sc);
        __syncwarp();
        if (lane == 0 && q >= 2) mbar_arrive(sb + B_EDONE);
        if (w4 == 0) STAMP(32 + q);
      }
      if (warp == 10) {
        unsigned* cnt = &g_hcnt[(cta & 3) * 32];
        mbar_wait(sb + B_EDONE, 0);
        if (lane == 0) { fence_rel(); red_add(cnt, 1); }
        __syncwarp();
        STAMP(47);
      }
      if (wg == 3) {
        check_stats(na, nc, sp + 512 * 3, tag);
        float4 sa[2], sc[2], ta, tc;
        ld_stats(sa[0], sc[0], sp); ld_stats(sa[1], sc[1], sp + 512); ld_stats(ta, tc, sp + 1024);
#pragma unroll 1
        for (int q = 0; q < 4; q += 2) {
          float y[4][4];
          uint32_t xl[4], xh[4];
#pragma unroll
          for (int i = 0; i < 4; i++) { const uint32_t a = xa + (q + (i >> 1)) * 8 * REC + (3 + (i & 1)) * xs; xl[i] = lds32(a); xh[i] = lds32(a + REC); }
          if (q) mbar_wait(sb + B_EDONE, 0);
          mbar_wait(sb + B_YRDY + 8 * q + 8, 1);
          wg_fence();
#pragma unroll
          for (int i = 0; i < 4; i++) red_sum(y[i], da + (q + (i >> 1)) * 64 + (1 + (i & 1)) * (4 * PR / 16), db);
          wg_commit();
          wg_wait<0>();
#pragma unroll
          for (int i = 0; i < 4; i++) red_fin(hp + (q + (i >> 1)) * 256 + (3 + (i & 1)) * 131072, y[i], xl[i], xh[i], sa[i >> 1], sc[i >> 1]);
          sa[0] = ta; sc[0] = tc; sa[1] = na; sc[1] = nc;
          if (w4 == 0) STAMP(36 + q);
        }
        __syncwarp();
        if (lane == 0) mbar_arrive(sb + B_CDONE);
        const int lid = logical_id(), m = TILE_M(lid), f = TILE_F(lid);
        if (w4 < 2) {
          mbar_wait(sb + B_CDONE, 0);
          if (elect1()) {
#pragma unroll 1
            for (int u = 3 * w4; u < 3 * w4 + 3; u++) {
              const int kg = 6 * m + u, nb = kg >> 3;
              tma2d(sb + 9 * 16384 + u * 2688, &tm.w2, 160 * (f >> 1), 64 * (3 * (2 * (nb & 3) + (f & 1)) + (nb >> 2)) + 8 * (kg & 7), sb + B_W2G);
            }
            mbar_expect(sb + B_W2G, 3 * 2688);
          }
          __syncwarp();
        }
        uint4 wv[8];
        uint32_t wo[8];
        mbar_wait(sb + B_W2G, 0);
#pragma unroll
        for (int i = 0; i < 8; i++) {
          const int cm = min(16 * i + ((tid & 127) >> 3), 119), u = (cm * 205) >> 12, cg = cm - 20 * u, hi = cg >= 10, keep = (hi ^ f ^ 1) & 1, kg = 6 * m + u;
          wv[i] = lds128(sb + 9 * 16384 + u * 2688 + (lane & 7) * 336 + cg * 16);
          wo[i] = f * 245760 + (kg < 64 ? kg * 2560 + keep * 1280 : 163840 + keep * 40960 + (kg - 64) * 1280) + (cg - 10 * hi) * 128 + (lane & 7) * 16;
        }
        bar_arrive(7, 160);
    {
      const uint32_t a0 = sb + OFF_A + (f >> 2) * 8192 + (16 * w4 + (lane & 15)) * 128 + (((2 * (f & 3) + (lane >> 4)) ^ (lane & 7)) << 4);
      float s0 = 0.f, q0 = 0.f, s1 = 0.f, q1 = 0.f;
#pragma unroll 1
      for (int kb = 0; kb < 10; kb += 2) {
        uint32_t v[8];
        mbar_wait(sb + B_AFULL + 8 * kb, 1);
        ldsm4t(a0 + kb * 16384, v[0], v[1], v[2], v[3]);
        mbar_wait(sb + B_AFULL + 8 * kb + 8, 1);
        ldsm4t(a0 + kb * 16384 + 16384, v[4], v[5], v[6], v[7]);
#pragma unroll
        for (int i = 0; i < 8; i++) {
          const float a = bflo(v[i]), b = bfhi(v[i]);
          if (i & 2) { s1 += a + b; q1 = fmaf(a, a, fmaf(b, b, q1)); } else { s0 += a + b; q0 = fmaf(a, a, fmaf(b, b, q0)); }
        }
      }
      const bool o1 = lane & 1;
      float s = (o1 ? s1 : s0) + __shfl_xor_sync(0xffffffff, o1 ? s0 : s1, 1), q = (o1 ? q1 : q0) + __shfl_xor_sync(0xffffffff, o1 ? q0 : q1, 1);
      s += __shfl_xor_sync(0xffffffff, s, 2); q += __shfl_xor_sync(0xffffffff, q, 2);
      if (!(lane & 2)) st_relaxed64(&g_stat2[(128 * m + 16 * f + 8 * (lane & 1) + (lane >> 2)) * 4 + w4], (__float_as_uint(s) & ~3u) | (tag & 3), __float_as_uint(q));
      const float2* p = g_stat2 + (128 * m + (tid & 127)) * 4;
      float4 u, v;
      unsigned c = 0;
      for (;;) {
        if (LN2SLEEP) __nanosleep(LN2SLEEP);
        asm volatile("ld.relaxed.gpu.global.v4.f32 {%0,%1,%2,%3}, [%4];" : "=f"(u.x), "=f"(u.y), "=f"(u.z), "=f"(u.w) : "l"(p) : "memory");
        asm volatile("ld.relaxed.gpu.global.v4.f32 {%0,%1,%2,%3}, [%4];" : "=f"(v.x), "=f"(v.y), "=f"(v.z), "=f"(v.w) : "l"(p + 2) : "memory");
        const uint32_t bad = (__float_as_uint(u.x) ^ tag) | (__float_as_uint(u.z) ^ tag) | (__float_as_uint(v.x) ^ tag) | (__float_as_uint(v.z) ^ tag);
        if (__all_sync(0xffffffff, (bad & 3) == 0)) break;
        SPIN_GUARD(c);
      }
      const float mean = ((u.x + u.z) + (v.x + v.z)) * (1.f / 640.f);
      sts64f(sb + OFF_ST2 + (tid & 127) * 8, rsqrtf(fmaxf(((u.y + u.w) + (v.y + v.w)) * (1.f / 640.f) - mean * mean, 0.f) + LN_EPS), mean);
      __syncwarp();
      if (lane == 0) mbar_arrive(sb + B_S2);
      if (w4 == 0) STAMP(49);
    }
        if (W2SLEEP) __nanosleep(W2SLEEP);
#pragma unroll
        for (int i = 0; i < 8; i++) { stg128(g_w2t + wo[i], wv[i]); if (W2GAP) __nanosleep(W2GAP); }
        bar_arrive(3, 416);
        if (w4 == 0) STAMP(28);
      }
    }
    if (CR < 216) asm volatile("setmaxnreg.dec.sync.aligned.u32 40;");
    if (wgsel == 2) {
    ROLE_IDS
    const unsigned epoch = lds32(sb + OFF_EP);
    const int lid = logical_id(), m = TILE_M(lid), f = TILE_F(lid);
    if (w4 == 0) {
      if (elect1()) {
        int c0 = 192 * f, r0 = 4;
        unsigned w2c = 0;
#pragma unroll 1
        for (int s = 4; s < 30; s++) {
          const uint32_t sl = s & 3;
          wait_w13(sb + B_WEMPTY + 8 * sl, ((s >> 2) & 1) ^ 1, sb + OFF_W + sl * 16384, sb + OFF_W + sl * 16384 + 8192, &tm.w1, &tm.w3,
                   c0, (r0 & 1) * 64, r0 >> 1, sb + B_WFULL + 8 * sl);
          r0++;
          if (XE && s == 5) { r0 = 0; c0 += 64; }
          if (XE && s == 5 + XE) { r0 = 6; c0 -= 64; }
          if (s == 9 + XE) { r0 = XE; c0 += 64; }
          if (s == 19) { r0 = 0; c0 += 64; }
          if (s == 28) w2c = ld_relaxed(&g_w2cnt[f * 32]);
        }
        unsigned c = 0;
        while ((int)(w2c - 16 * epoch) < 0) { w2c = ld_relaxed(&g_w2cnt[f * 32]); SPIN_GUARD(c); }
        fence_async_g();
        uint32_t r = 0, ph = 0;
#pragma unroll 1
        for (int s = 0; s < 16; s++) {
          const uint32_t buf = r < 4 ? 2 + ((r + 2) & 3) : r - 4;
          const uint32_t bf = sb + (r < 4 ? B_WFULL - 16 : B_AFULL + 64) + 8 * buf, be = sb + (r < 4 ? B_WEMPTY - 16 : B_AEMPTY + 64) + 8 * buf;
          wait_bulk(be, ph ^ ((r & 6) == 2 ? 1 : 0), sb + OFF_W - 32768 + buf * 16384, g_w2t + f * 245760 + s * 15360, 15360, bf);
          if (++r == 6) { r = 0; ph ^= 1; }
        }
      }
    } else if (w4 == 1) {
#pragma unroll 1
      for (int st = 0; st < 3; st++) {
        if (st < 2) { mbar_wait(sb + (st ? B_CDONE : B_EDONE), 0); fence_async_s(); }
        if (st == 1 && A1AFT) bar_sync(8, 64);
        if (st == 2) bar_sync(7, 160);
        if (st != 1) {
          unsigned c = 0;
          const unsigned* cp = &g_hcnt[(2 * st + (lane & 3)) * 32];
          while (!__all_sync(0xffffffff, (int)(ld_relaxed(cp) - 32 * epoch) >= 0)) SPIN_GUARD(c);
          fence_async_g();
        }
        STAMP(50 + st);
        if (elect1()) {
#pragma unroll 1
          for (int kb = 3 * st; kb < (st == 2 ? 10 : 3 * st + 3); kb++) {
            tma2d(sb + OFF_A + kb * 16384, &tm.h, 128 * m, 64 * kb, sb + B_AFULL + 8 * kb);
            tma2d(sb + OFF_A + kb * 16384 + 8192, &tm.h, 128 * m + 64, 64 * kb, sb + B_AFULL + 8 * kb);
            mbar_expect(sb + B_AFULL + 8 * kb, 16384);
          }
        }
        __syncwarp();
      }
      STAMP(24);
      mbar_wait(sb + B_AEMPTY, 0);
#pragma unroll 1
      for (int p = 0; p < 3; p++) {
        unsigned c = 0;
        while (!__all_sync(0xffffffff, ld_relaxed(&g_gflag[m * 32 + p * 8 + 2 * (lane & 3) + (f & 1)]) == epoch)) SPIN_GUARD(c);
        STAMP(25 + p);
        fence_async_g();
        if (elect1()) {
#pragma unroll 1
          for (int j = 0; j < 4; j++) {
            const uint32_t s = (4 * p + j) & 7, fp = 2 * j + (f & 1);
            wait_bulk(sb + B_AEMPTY + 8 * s, p >> 1, sb + OFF_A + s * 16384, g_g + (m * 24 + 3 * fp + p) * 16384, 16384, sb + B_AFULL + 8 * s);
          }
        }
        __syncwarp();
      }
      mbar_wait(sb + B_AEMPTY + 56, 1);
      if (elect1()) {
#pragma unroll
        for (int i = 0; i < 2; i++)
          asm volatile("cp.async.bulk.tensor.3d.shared::cluster.global.mbarrier::complete_tx::bytes [%0], [%1, {%3, %4, %5}], [%2];"
                       ::"r"(sb + OFF_A + 4 * 16384 + 20480 + i * 10240), "l"(&tm.hr), "r"(sb + B_AFULL + 56), "r"(128 * m + 64 * i), "r"(0), "r"(16 * f) : "memory");
        mbar_expect(sb + B_AFULL + 56, 20480);
      }
    } else {
      if (w4 == 3) {
        mbar_wait(sb + B_EDONE, 0);
        if (elect1()) {
          tma3d(sb + OFF_W + 49152, &tm.w1, 192 * f, 3, sb + B_WFULL + 24);
          tma3d(sb + OFF_W + 49152 + 8192, &tm.w3, 192 * f, 3, sb + B_WFULL + 24);
          mbar_expect(sb + B_WFULL + 24, 16384);
        }
        __syncwarp();
        mbar_wait(sb + B_AFULL, 1);
#pragma unroll 1
        for (int p = 0; p < 3; p++) fetch_colsum(sb, f, p, lane, epoch);
      } else {
        mbar_wait(sb + B_CDONE, 0);
        if (lane == 0) { fence_rel(); red_add(&g_hcnt[(4 + (lid & 3)) * 32], 1); }
        __syncwarp();
        if (A1AFT) bar_arrive(8, 64);
        STAMP(48);
#pragma unroll 1
        for (int p = 0; p < 3; p++) {
          bar_sync(3 + p, p ? 288 : 416);
          if (lane == 0) { fence_rel(); st_relaxed(&g_gflag[m * 32 + p * 8 + f], epoch); if (p == 0) red_add(&g_w2cnt[f * 32], 1); }
          __syncwarp();
          STAMP(20 + p);
        }
      }
    }
    }
  }
}

typedef CUresult (*EncFn)(CUtensorMap*, CUtensorMapDataType, cuuint32_t, void*, const cuuint64_t*, const cuuint64_t*,
                          const cuuint32_t*, const cuuint32_t*, CUtensorMapInterleave, CUtensorMapSwizzle,
                          CUtensorMapL2promotion, CUtensorMapFloatOOBfill);

void make_map2(EncFn enc, CUtensorMap* tm, void* p, uint64_t inner, uint64_t outer) {
  cuuint64_t gd[2] = {inner, outer}, gs[1] = {inner * 2};
  cuuint32_t bd[2] = {64, 64}, es[2] = {1, 1};
  enc(tm, CU_TENSOR_MAP_DATA_TYPE_BFLOAT16, 2, p, gd, gs, bd, es, CU_TENSOR_MAP_INTERLEAVE_NONE, CU_TENSOR_MAP_SWIZZLE_128B,
      CU_TENSOR_MAP_L2_PROMOTION_L2_128B, CU_TENSOR_MAP_FLOAT_OOB_FILL_NONE);
}
void make_map3(EncFn enc, CUtensorMap* tm, void* p) {
  cuuint64_t gd[3] = {1536, 128, 5}, gs[2] = {5 * 3072, 3072};
  cuuint32_t bd[3] = {64, 64, 1}, es[3] = {1, 1, 1};
  enc(tm, CU_TENSOR_MAP_DATA_TYPE_BFLOAT16, 3, p, gd, gs, bd, es, CU_TENSOR_MAP_INTERLEAVE_NONE, CU_TENSOR_MAP_SWIZZLE_128B,
      CU_TENSOR_MAP_L2_PROMOTION_L2_128B, CU_TENSOR_MAP_FLOAT_OOB_FILL_NONE);
}
void make_map4(EncFn enc, CUtensorMap* tm, void* p, bool wide, bool halo, bool perm = false) {
  cuuint64_t gd[4] = {640, 2, 128, 8}, gs[3] = {perm ? 8 * 1280u : 1280u, 16 * 1280, perm ? 1280u : 2 * 1280u};
  cuuint32_t bd[4] = {wide ? 32u : 16u, 2, halo ? 1u : 8u, halo ? 2u : 8u}, es[4] = {1, 1, 1, 1};
  enc(tm, CU_TENSOR_MAP_DATA_TYPE_BFLOAT16, 4, p, gd, gs, bd, es, CU_TENSOR_MAP_INTERLEAVE_NONE,
      wide ? CU_TENSOR_MAP_SWIZZLE_64B : CU_TENSOR_MAP_SWIZZLE_32B, CU_TENSOR_MAP_L2_PROMOTION_L2_128B, CU_TENSOR_MAP_FLOAT_OOB_FILL_NONE);
}

}

extern "C" void kernel_launch(void* const* d_in, const int* in_sizes, int n_in, void* d_out, int out_size) {
  (void)in_sizes; (void)n_in; (void)out_size;
  void* fn = nullptr;
  cudaDriverEntryPointQueryResult qr;
  cudaGetDriverEntryPoint("cuTensorMapEncodeTiled", &fn, cudaEnableDefault, &qr);
  EncFn enc = (EncFn)fn;
  void* hT = nullptr;
  cudaGetSymbolAddress(&hT, g_hT);
  Maps tm;
  make_map2(enc, &tm.h, hT, 2048, 640);
  {
    cuuint64_t gd[3] = {2048, 5, 128}, gs[2] = {128 * 4096, 4096};
    cuuint32_t bd[3] = {64, 5, 16}, es[3] = {1, 1, 1};
    enc(&tm.hr, CU_TENSOR_MAP_DATA_TYPE_BFLOAT16, 3, hT, gd, gs, bd, es, CU_TENSOR_MAP_INTERLEAVE_NONE, CU_TENSOR_MAP_SWIZZLE_128B,
        CU_TENSOR_MAP_L2_PROMOTION_L2_128B, CU_TENSOR_MAP_FLOAT_OOB_FILL_NONE);
  }
  {
    cuuint64_t gd[2] = {640, 1536}, gs[1] = {1280};
    cuuint32_t bd[2] = {168, 8}, es[2] = {1, 1};
    enc(&tm.w2, CU_TENSOR_MAP_DATA_TYPE_BFLOAT16, 2, d_in[9], gd, gs, bd, es, CU_TENSOR_MAP_INTERLEAVE_NONE, CU_TENSOR_MAP_SWIZZLE_NONE,
        CU_TENSOR_MAP_L2_PROMOTION_L2_128B, CU_TENSOR_MAP_FLOAT_OOB_FILL_NONE);
  }
  make_map3(enc, &tm.w1, d_in[7]);
  make_map3(enc, &tm.w3, d_in[8]);
  for (int w = 0; w < 2; w++) {
    make_map4(enc, &tm.c[w][0], d_in[1], w, false);
    make_map4(enc, &tm.c[w][1], d_in[2], w, false);
    make_map4(enc, &tm.c[w][2], d_in[0], w, false);
    make_map4(enc, &tm.c[w][3], d_in[1], w, true);
    make_map4(enc, &tm.c[w][4], d_in[2], w, true);
  }
  Params p;
  p.x = (const __nv_bfloat16*)d_in[0]; p.k = (const __nv_bfloat16*)d_in[1]; p.v = (const __nv_bfloat16*)d_in[2];
  p.shift = (const __nv_bfloat16*)d_in[3]; p.kf = (const __nv_bfloat16*)d_in[4]; p.D = (const __nv_bfloat16*)d_in[5];
  p.w2 = (const __nv_bfloat16*)d_in[9];
  p.out = (__nv_bfloat16*)d_out; p.z = 0;
  cudaFuncSetAttribute(h3_ffn_kernel, cudaFuncAttributeMaxDynamicSharedMemorySize, SMEM_BYTES);
  h3_ffn_kernel<<<NCTA, 512, SMEM_BYTES>>>(p, tm);
}
```
